```python
import torch

def _softmax(x, axis=-1):
    return torch.softmax(x, dim=axis)
def _gelu(x):
    return torch.nn.functional.gelu(x, approximate="tanh")
def _silu(x):
    return torch.nn.functional.silu(x)
def _sigmoid(x):
    return torch.sigmoid(x)
def _layernorm(x, axis=-1, eps=1e-5):
    m = x.mean(dim=axis, keepdim=True)
    v = x.var(dim=axis, keepdim=True, unbiased=False)
    return (x - m) / torch.sqrt(v + eps)
def _scatter_add(tgt, idx, src, axis=0):
    return tgt.clone().index_add_(axis, idx, src)
def _segment_sum(src, seg, n):
    out = torch.zeros((n,) + src.shape[1:], dtype=src.dtype)
    return out.index_add_(0, seg, src)
def _pad(x, pw):
    flat = tuple(v for pair in reversed(pw) for v in pair)
    return torch.nn.functional.pad(x, flat)

kernel_name = 'gated_mix__spectral_gfnet__glu_gated_reglu__prompt'

def setup_inputs():

    _w = (lambda a: (lambda t: t.to(torch.bfloat16) if t.is_floating_point() else t)(torch.as_tensor(a)))
    def _A_setup():
        B, S, D = 1, 2048, 640
        Df = D // 2 + 1
        return {
            "x": _w((lambda *s: torch.randn(*s, dtype=torch.bfloat16) * 0.05)(B, S, D)),
            "w_r": _w((lambda *s: torch.randn(*s, dtype=torch.bfloat16) * 0.05)(S, Df) * 0.02),
            "w_i": _w((lambda *s: torch.randn(*s, dtype=torch.bfloat16) * 0.05)(S, Df) * 0.02),
        }
    _A_in = _A_setup()

    def _B_setup():
        B, S, D, F = 1, 2048, 640, 1728
        return {
            "x": _w((lambda *s: torch.randn(*s, dtype=torch.bfloat16) * 0.05)(B, S, D)),
            "W_gate": _w((lambda *s: torch.randn(*s, dtype=torch.bfloat16) * 0.2)(D, F) * (2.0 / D) ** 0.5),
            "W_up": _w((lambda *s: torch.randn(*s, dtype=torch.bfloat16) * 0.2)(D, F) * (2.0 / D) ** 0.5),
            "W_down": _w((lambda *s: torch.randn(*s, dtype=torch.bfloat16) * 0.2)(F, D) * (1.0 / F) ** 0.5),
        }
    _B_in = _B_setup()

    return {
        "A_x": _A_in["x"],
        "A_w_r": _A_in["w_r"],
        "A_w_i": _A_in["w_i"],
        "B_x": _B_in["x"],
        "B_W_gate": _B_in["W_gate"],
        "B_W_up": _B_in["W_up"],
        "B_W_down": _B_in["W_down"],
        "gate_w": _w((lambda *s: torch.randn(*s, dtype=torch.bfloat16) * 0.05)(640) * 16.0),
    }

def reference(A_x, A_w_r, A_w_i, B_x, B_W_gate, B_W_up, B_W_down, gate_w):
    def _A_ref(x, w_r, w_i):
        B, S, D = x.shape
        X = (lambda x, axes=(-2,-1): torch.fft.rfft2(x.float(), dim=axes))(x, axes=(-2, -1))
        W = w_r + 1j * w_i
        X = X * W
        y = (lambda x, s, axes=(-2,-1): torch.fft.irfft2(x, s=s, dim=axes).to(torch.bfloat16))(X, (S, D), axes=(-2, -1))
        return y

    def _B_ref(x, W_gate, W_up, W_down):
        gate = torch.einsum("bsd,df->bsf", x, W_gate)
        up = torch.einsum("bsd,df->bsf", x, W_up)
        gate = gate * (lambda x, dt: x.to(dt))(gate > 0, gate.dtype)
        h = gate * up
        return torch.einsum("bsf,fd->bsd", h, W_down)

    x = A_x
    g = _sigmoid((x * gate_w).sum(-1, keepdims=True))
    a = _A_ref(x, A_w_r, A_w_i)
    b = _B_ref(x, B_W_gate, B_W_up, B_W_down)
    return g * a + (1 - g) * b
```

```cpp
#include <cuda_runtime.h>
#include <cuda_bf16.h>
#include <cuda.h>
#include <stdint.h>
#include <stddef.h>

namespace {

constexpr int D_ = 640, DF_ = 321;
constexpr int NCTA = 132;
constexpr int NSTAGE = 4;
constexpr int STAGE_BYTES = 49152;
constexpr int OFF_STG = NSTAGE * STAGE_BYTES;
constexpr int OFF_BAR = OFF_STG + 32768;
constexpr int OFF_G = OFF_BAR + 256;
constexpr int OFF_END = OFF_G + 1024 + 256;
#define WKB_NS 32
#define STORE_DELAY 0
#define NFIRST 3
#define WJOB_KB 0
#define WJOB_STEP 0
#define WDPF_KB 8
constexpr int SMEM_BYTES = OFF_END + 1024;

constexpr uint16_t COS640[640] = {
  16256,16256,16256,16256,16256,16256,16256,16255,16255,16255,16255,16255,16254,16254,16254,16253,16253,16252,16252,16252,
  16251,16251,16250,16250,16249,16248,16248,16247,16246,16246,16245,16244,16243,16243,16242,16241,16240,16239,16238,16237,
  16237,16236,16235,16234,16232,16231,16230,16229,16228,16227,16226,16225,16223,16222,16221,16220,16218,16217,16216,16214,
  16213,16211,16210,16209,16207,16206,16204,16203,16201,16199,16198,16196,16195,16193,16191,16190,16188,16186,16185,16183,
  16181,16179,16177,16176,16174,16172,16170,16168,16166,16164,16162,16160,16158,16157,16155,16152,16150,16148,16146,16144,
  16142,16140,16138,16136,16134,16132,16129,16127,16122,16118,16113,16109,16104,16100,16095,16091,16086,16082,16077,16073,
  16068,16063,16059,16054,16049,16044,16040,16035,16030,16025,16021,16016,16011,16006,16001,15993,15983,15973,15963,15954,
  15944,15934,15924,15914,15904,15894,15884,15874,15857,15837,15817,15797,15777,15757,15729,15689,15649,15601,15521,15393,
  0,48161,48289,48369,48417,48457,48497,48525,48545,48565,48585,48605,48625,48642,48652,48662,48672,48682,48692,48702,
  48712,48722,48731,48741,48751,48761,48769,48774,48779,48784,48789,48793,48798,48803,48808,48812,48817,48822,48827,48831,
  48836,48841,48845,48850,48854,48859,48863,48868,48872,48877,48881,48886,48890,48895,48897,48900,48902,48904,48906,48908,
  48910,48912,48914,48916,48918,48920,48923,48925,48926,48928,48930,48932,48934,48936,48938,48940,48942,48944,48945,48947,
  48949,48951,48953,48954,48956,48958,48959,48961,48963,48964,48966,48967,48969,48971,48972,48974,48975,48977,48978,48979,
  48981,48982,48984,48985,48986,48988,48989,48990,48991,48993,48994,48995,48996,48997,48998,48999,49000,49002,49003,49004,
  49005,49005,49006,49007,49008,49009,49010,49011,49011,49012,49013,49014,49014,49015,49016,49016,49017,49018,49018,49019,
  49019,49020,49020,49020,49021,49021,49022,49022,49022,49023,49023,49023,49023,49023,49024,49024,49024,49024,49024,49024,
  49024,49024,49024,49024,49024,49024,49024,49023,49023,49023,49023,49023,49022,49022,49022,49021,49021,49020,49020,49020,
  49019,49019,49018,49018,49017,49016,49016,49015,49014,49014,49013,49012,49011,49011,49010,49009,49008,49007,49006,49005,
  49005,49004,49003,49002,49000,48999,48998,48997,48996,48995,48994,48993,48991,48990,48989,48988,48986,48985,48984,48982,
  48981,48979,48978,48977,48975,48974,48972,48971,48969,48967,48966,48964,48963,48961,48959,48958,48956,48954,48953,48951,
  48949,48947,48945,48944,48942,48940,48938,48936,48934,48932,48930,48928,48926,48925,48923,48920,48918,48916,48914,48912,
  48910,48908,48906,48904,48902,48900,48897,48895,48890,48886,48881,48877,48872,48868,48863,48859,48854,48850,48845,48841,
  48836,48831,48827,48822,48817,48812,48808,48803,48798,48793,48789,48784,48779,48774,48769,48761,48751,48741,48731,48722,
  48712,48702,48692,48682,48672,48662,48652,48642,48625,48605,48585,48565,48545,48525,48497,48457,48417,48369,48289,48161,
  0,15393,15521,15601,15649,15689,15729,15757,15777,15797,15817,15837,15857,15874,15884,15894,15904,15914,15924,15934,
  15944,15954,15963,15973,15983,15993,16001,16006,16011,16016,16021,16025,16030,16035,16040,16044,16049,16054,16059,16063,
  16068,16073,16077,16082,16086,16091,16095,16100,16104,16109,16113,16118,16122,16127,16129,16132,16134,16136,16138,16140,
  16142,16144,16146,16148,16150,16152,16155,16157,16158,16160,16162,16164,16166,16168,16170,16172,16174,16176,16177,16179,
  16181,16183,16185,16186,16188,16190,16191,16193,16195,16196,16198,16199,16201,16203,16204,16206,16207,16209,16210,16211,
  16213,16214,16216,16217,16218,16220,16221,16222,16223,16225,16226,16227,16228,16229,16230,16231,16232,16234,16235,16236,
  16237,16237,16238,16239,16240,16241,16242,16243,16243,16244,16245,16246,16246,16247,16248,16248,16249,16250,16250,16251,
  16251,16252,16252,16252,16253,16253,16254,16254,16254,16255,16255,16255,16255,16255,16256,16256,16256,16256,16256,16256,

};
constexpr float COS2048Q[513] = {
  1.000000000e+00f,9.999952912e-01f,9.999811649e-01f,9.999576211e-01f,9.999247193e-01f,9.998823404e-01f,9.998306036e-01f,9.997693896e-01f,
  9.996988177e-01f,9.996188283e-01f,9.995294213e-01f,9.994305968e-01f,9.993223548e-01f,9.992047548e-01f,9.990777373e-01f,9.989413023e-01f,
  9.987954497e-01f,9.986402392e-01f,9.984755516e-01f,9.983015656e-01f,9.981181026e-01f,9.979252815e-01f,9.977230430e-01f,9.975114465e-01f,
  9.972904325e-01f,9.970600605e-01f,9.968202710e-01f,9.965711236e-01f,9.963126183e-01f,9.960446954e-01f,9.957674146e-01f,9.954807758e-01f,
  9.951847196e-01f,9.948793054e-01f,9.945645928e-01f,9.942404628e-01f,9.939069748e-01f,9.935641289e-01f,9.932119250e-01f,9.928504229e-01f,
  9.924795628e-01f,9.920992851e-01f,9.917097688e-01f,9.913108349e-01f,9.909026623e-01f,9.904850721e-01f,9.900581837e-01f,9.896219969e-01f,
  9.891765118e-01f,9.887216687e-01f,9.882575870e-01f,9.877841473e-01f,9.873014092e-01f,9.868093729e-01f,9.863080978e-01f,9.857975245e-01f,
  9.852776527e-01f,9.847484827e-01f,9.842100739e-01f,9.836624265e-01f,9.831054807e-01f,9.825392962e-01f,9.819638729e-01f,9.813792109e-01f,
  9.807852507e-01f,9.801821113e-01f,9.795697927e-01f,9.789481759e-01f,9.783173800e-01f,9.776773453e-01f,9.770281315e-01f,9.763697386e-01f,
  9.757021070e-01f,9.750253558e-01f,9.743393660e-01f,9.736442566e-01f,9.729399681e-01f,9.722265005e-01f,9.715039134e-01f,9.707721472e-01f,
  9.700312614e-01f,9.692812562e-01f,9.685220718e-01f,9.677538276e-01f,9.669764638e-01f,9.661899805e-01f,9.653944373e-01f,9.645897746e-01f,
  9.637760520e-01f,9.629532695e-01f,9.621214271e-01f,9.612804651e-01f,9.604305029e-01f,9.595715404e-01f,9.587034583e-01f,9.578264356e-01f,
  9.569403529e-01f,9.560452700e-01f,9.551411867e-01f,9.542281032e-01f,9.533060193e-01f,9.523749948e-01f,9.514350295e-01f,9.504860640e-01f,
  9.495281577e-01f,9.485613704e-01f,9.475855827e-01f,9.466009140e-01f,9.456073046e-01f,9.446048141e-01f,9.435934424e-01f,9.425731897e-01f,
  9.415440559e-01f,9.405060410e-01f,9.394592047e-01f,9.384035468e-01f,9.373390079e-01f,9.362656474e-01f,9.351835251e-01f,9.340925217e-01f,
  9.329928160e-01f,9.318842888e-01f,9.307669401e-01f,9.296408892e-01f,9.285060763e-01f,9.273625016e-01f,9.262102246e-01f,9.250492454e-01f,
  9.238795042e-01f,9.227011204e-01f,9.215140343e-01f,9.203183055e-01f,9.191138744e-01f,9.179008007e-01f,9.166790843e-01f,9.154487252e-01f,
  9.142097831e-01f,9.129621983e-01f,9.117060304e-01f,9.104412794e-01f,9.091680050e-01f,9.078860879e-01f,9.065957069e-01f,9.052967429e-01f,
  9.039893150e-01f,9.026733041e-01f,9.013488293e-01f,9.000158906e-01f,8.986744881e-01f,8.973245621e-01f,8.959662318e-01f,8.945994973e-01f,
  8.932242990e-01f,8.918406963e-01f,8.904487491e-01f,8.890483379e-01f,8.876396418e-01f,8.862225413e-01f,8.847970963e-01f,8.833633661e-01f,
  8.819212914e-01f,8.804708719e-01f,8.790122271e-01f,8.775452971e-01f,8.760700822e-01f,8.745866418e-01f,8.730949759e-01f,8.715950847e-01f,
  8.700869679e-01f,8.685706854e-01f,8.670462370e-01f,8.655136228e-01f,8.639728427e-01f,8.624239564e-01f,8.608669639e-01f,8.593018055e-01f,
  8.577286005e-01f,8.561473489e-01f,8.545579910e-01f,8.529605865e-01f,8.513551950e-01f,8.497417569e-01f,8.481203318e-01f,8.464909196e-01f,
  8.448535800e-01f,8.432082534e-01f,8.415549994e-01f,8.398938179e-01f,8.382247090e-01f,8.365477324e-01f,8.348628879e-01f,8.331701756e-01f,
  8.314695954e-01f,8.297612071e-01f,8.280450702e-01f,8.263210654e-01f,8.245893121e-01f,8.228498101e-01f,8.211025000e-01f,8.193475008e-01f,
  8.175848126e-01f,8.158144355e-01f,8.140363097e-01f,8.122506142e-01f,8.104571700e-01f,8.086561561e-01f,8.068475723e-01f,8.050313592e-01f,
  8.032075167e-01f,8.013761640e-01f,7.995372415e-01f,7.976908684e-01f,7.958369255e-01f,7.939754725e-01f,7.921065688e-01f,7.902302146e-01f,
  7.883464098e-01f,7.864552140e-01f,7.845565677e-01f,7.826505899e-01f,7.807372212e-01f,7.788165212e-01f,7.768884897e-01f,7.749531269e-01f,
  7.730104327e-01f,7.710605264e-01f,7.691033483e-01f,7.671388984e-01f,7.651672363e-01f,7.631884217e-01f,7.612023950e-01f,7.592092156e-01f,
  7.572088242e-01f,7.552013993e-01f,7.531868219e-01f,7.511651516e-01f,7.491363883e-01f,7.471005917e-01f,7.450577617e-01f,7.430079579e-01f,
  7.409511209e-01f,7.388873100e-01f,7.368165851e-01f,7.347388864e-01f,7.326542735e-01f,7.305627465e-01f,7.284643650e-01f,7.263591290e-01f,
  7.242470980e-01f,7.221282125e-01f,7.200025320e-01f,7.178700566e-01f,7.157308459e-01f,7.135848403e-01f,7.114322186e-01f,7.092728019e-01f,
  7.071067691e-01f,7.049340606e-01f,7.027547359e-01f,7.005687952e-01f,6.983762383e-01f,6.961771250e-01f,6.939714551e-01f,6.917592287e-01f,
  6.895405650e-01f,6.873153448e-01f,6.850836873e-01f,6.828455329e-01f,6.806010008e-01f,6.783500314e-01f,6.760926843e-01f,6.738290191e-01f,
  6.715589762e-01f,6.692826152e-01f,6.669999361e-01f,6.647109985e-01f,6.624158025e-01f,6.601143479e-01f,6.578066945e-01f,6.554928422e-01f,
  6.531728506e-01f,6.508466601e-01f,6.485143900e-01f,6.461760402e-01f,6.438315511e-01f,6.414810419e-01f,6.391244531e-01f,6.367618442e-01f,
  6.343932748e-01f,6.320187449e-01f,6.296382546e-01f,6.272518039e-01f,6.248595119e-01f,6.224612594e-01f,6.200572252e-01f,6.176472902e-01f,
  6.152315736e-01f,6.128100753e-01f,6.103827953e-01f,6.079497933e-01f,6.055110693e-01f,6.030666232e-01f,6.006164551e-01f,5.981606841e-01f,
  5.956993103e-01f,5.932322741e-01f,5.907596946e-01f,5.882815719e-01f,5.857978463e-01f,5.833086371e-01f,5.808139443e-01f,5.783137679e-01f,
  5.758081675e-01f,5.732971430e-01f,5.707807541e-01f,5.682589412e-01f,5.657318234e-01f,5.631993413e-01f,5.606615543e-01f,5.581185222e-01f,
  5.555702448e-01f,5.530167222e-01f,5.504579544e-01f,5.478940606e-01f,5.453249812e-01f,5.427507758e-01f,5.401714444e-01f,5.375870466e-01f,
  5.349976420e-01f,5.324031115e-01f,5.298036337e-01f,5.271991491e-01f,5.245896578e-01f,5.219752789e-01f,5.193560123e-01f,5.167317986e-01f,
  5.141027570e-01f,5.114688277e-01f,5.088301301e-01f,5.061866641e-01f,5.035383701e-01f,5.008853674e-01f,4.982276559e-01f,4.955652654e-01f,
  4.928981960e-01f,4.902264774e-01f,4.875501692e-01f,4.848692417e-01f,4.821837842e-01f,4.794937670e-01f,4.767992198e-01f,4.741002023e-01f,
  4.713967443e-01f,4.686888158e-01f,4.659765065e-01f,4.632597864e-01f,4.605387151e-01f,4.578132927e-01f,4.550835788e-01f,4.523495734e-01f,
  4.496113360e-01f,4.468688369e-01f,4.441221356e-01f,4.413712621e-01f,4.386162460e-01f,4.358570874e-01f,4.330938160e-01f,4.303264916e-01f,
  4.275550842e-01f,4.247796834e-01f,4.220002592e-01f,4.192169011e-01f,4.164295495e-01f,4.136383235e-01f,4.108431637e-01f,4.080441594e-01f,
  4.052413106e-01f,4.024346471e-01f,3.996241987e-01f,3.968099952e-01f,3.939920366e-01f,3.911703825e-01f,3.883450329e-01f,3.855160475e-01f,
  3.826834261e-01f,3.798471987e-01f,3.770074248e-01f,3.741640747e-01f,3.713172078e-01f,3.684668243e-01f,3.656129837e-01f,3.627557158e-01f,
  3.598950505e-01f,3.570309579e-01f,3.541635275e-01f,3.512927592e-01f,3.484186828e-01f,3.455413282e-01f,3.426607251e-01f,3.397768736e-01f,
  3.368898630e-01f,3.339996636e-01f,3.311063051e-01f,3.282098472e-01f,3.253102899e-01f,3.224076927e-01f,3.195020258e-01f,3.165933788e-01f,
  3.136817515e-01f,3.107671440e-01f,3.078496456e-01f,3.049292266e-01f,3.020059466e-01f,2.990798354e-01f,2.961508930e-01f,2.932191491e-01f,
  2.902846634e-01f,2.873474658e-01f,2.844075263e-01f,2.814649343e-01f,2.785196900e-01f,2.755718231e-01f,2.726213634e-01f,2.696683109e-01f,
  2.667127550e-01f,2.637546659e-01f,2.607941031e-01f,2.578310966e-01f,2.548656464e-01f,2.518978119e-01f,2.489276081e-01f,2.459550500e-01f,
  2.429801822e-01f,2.400030196e-01f,2.370236069e-01f,2.340419590e-01f,2.310581058e-01f,2.280720770e-01f,2.250839174e-01f,2.220936269e-01f,
  2.191012353e-01f,2.161068022e-01f,2.131103128e-01f,2.101118416e-01f,2.071113735e-01f,2.041089684e-01f,2.011046410e-01f,1.980984062e-01f,
  1.950903237e-01f,1.920803934e-01f,1.890686601e-01f,1.860551536e-01f,1.830398887e-01f,1.800228953e-01f,1.770042181e-01f,1.739838719e-01f,
  1.709618866e-01f,1.679382920e-01f,1.649131179e-01f,1.618863940e-01f,1.588581502e-01f,1.558284014e-01f,1.527971923e-01f,1.497645378e-01f,
  1.467304677e-01f,1.436950266e-01f,1.406582445e-01f,1.376201212e-01f,1.345807016e-01f,1.315400302e-01f,1.284981072e-01f,1.254549772e-01f,
  1.224106774e-01f,1.193652153e-01f,1.163186282e-01f,1.132709533e-01f,1.102222055e-01f,1.071724221e-01f,1.041216329e-01f,1.010698602e-01f,
  9.801714122e-02f,9.496349841e-02f,9.190895408e-02f,8.885355294e-02f,8.579730988e-02f,8.274026215e-02f,7.968243957e-02f,7.662386447e-02f,
  7.356456667e-02f,7.050457597e-02f,6.744392216e-02f,6.438262761e-02f,6.132073700e-02f,5.825826526e-02f,5.519524589e-02f,5.213170499e-02f,
  4.906767607e-02f,4.600318149e-02f,4.293825850e-02f,3.987292573e-02f,3.680722415e-02f,3.374117240e-02f,3.067480400e-02f,2.760814503e-02f,
  2.454122901e-02f,2.147408016e-02f,1.840673015e-02f,1.533920597e-02f,1.227153838e-02f,9.203754365e-03f,6.135884672e-03f,3.067956772e-03f,
  0.000000000e+00f,

};
constexpr float cos2048(int j) {
  j &= 2047;
  return j <= 512 ? COS2048Q[j] : j <= 1024 ? -COS2048Q[1024 - j] : j <= 1536 ? -COS2048Q[j - 1024] : COS2048Q[2048 - j];
}

constexpr uint16_t to_bf16(double x) {
  if (x == 0.0) return 0;
  const uint16_t sign = x < 0 ? 0x8000 : 0;
  double a = x < 0 ? -x : x;
  int e = 0;
  while (a < 1.0) { a *= 2.0; e--; }
  const double m = a * 128.0;
  int mi = (int)m;
  const double fr = m - mi;
  if (fr > 0.5 || (fr == 0.5 && (mi & 1))) mi++;
  if (mi == 256) { mi = 128; e++; }
  return (uint16_t)(sign | ((127 + e) << 7) | (mi - 128));
}

struct alignas(1024) TTab { uint16_t v[640][640]; };
constexpr TTab make_T() {
  TTab t{};
  for (int r = 0; r < 640; r++) {
    int k = (r == 0) ? 0 : (r == 1) ? 320 : (r < 4) ? 160 : (r & 2) ? 320 - (r >> 2) : (r >> 2);
    int idx = (r >= 2 && (r & 1)) ? 160 : 0;
    for (int d = 0; d < 640; d++) { t.v[r][d] = COS640[idx]; idx += k; if (idx >= 640) idx -= 640; }
  }
  return t;
}
__device__ const TTab g_T = make_T();

struct alignas(1024) CConst {
  uint16_t f64[8192];
  uint16_t m1[4096];
  uint16_t m4[4096];
  uint16_t tw[4096];
};
constexpr int swz(int row, int col) { return row * 64 + ((((col >> 3) ^ (row & 7)) << 3) | (col & 7)); }
constexpr CConst make_C() {
  CConst c{};
  for (int k = 0; k < 64; k++)
    for (int n = 0; n < 64; n++) {
      int a = (10 * k * n) % 640;
      c.f64[swz(k, n)] = COS640[a];
      c.f64[4096 + swz(k, n)] = COS640[(a + 160) % 640];
    }
  for (int m = 0; m < 64; m++) {
    int p = (m >> 4) * 8 + (m & 7), im_out = (m >> 3) & 1;
    for (int k = 0; k < 64; k++) {
      {
        int a = k & 31, im_in = k >> 5;
        int ang = (20 * p * a) % 640;
        uint16_t cs = COS640[ang], msn = COS640[(ang + 160) % 640], psn = COS640[(ang + 480) % 640];
        c.m1[swz(m, k)] = (im_out == im_in) ? cs : (im_out == 0 ? psn : msn);
      }
      {
        int pp = (k >> 4) * 8 + (k & 7), im_in = (k >> 3) & 1;
        int ang = (20 * p * pp) % 640;
        uint16_t cs = COS640[ang], msn = COS640[(ang + 160) % 640], psn = COS640[(ang + 480) % 640];
        c.m4[swz(m, k)] = (im_out == im_in) ? cs : (im_out == 0 ? msn : psn);
      }
    }
  }
  for (int j = 0; j < 8; j++)
    for (int tid = 0; tid < 128; tid++) {
      int w = tid >> 5, lane = tid & 31;
      int p = 8 * w + (lane >> 2), t = lane & 3;
      for (int e = 0; e < 2; e++) {
        int b = 8 * j + 2 * t + e;
        const int o = (((j >> 1) * 128 + tid) * 4 + (j & 1) * 2) * 2 + e;
        c.tw[o] = to_bf16((double)cos2048(p * b) * 1.2352647110032733e-03);
        c.tw[o + 2] = to_bf16((double)cos2048(p * b + 512) * 1.2352647110032733e-03);
      }
    }
  return c;
}
__device__ const CConst g_C = make_C();

struct alignas(1024) TETab { uint16_t v[40][5120]; };
constexpr TETab make_TE() {
  TETab t{};
  for (int n = 0; n < 4; n++)
    for (int grp = 0; grp < 2; grp++)
      for (int np = 0; np < 80; np++) {
        const int c = 16 * (np >> 3) + 8 * (np & 1) + 2 * ((np >> 1) & 3) + grp;
        const int d = 160 * n + ((n & 1) ? (c + 32) % 160 : c);
        int a = 0;
        for (int slot = 0; slot < 160; slot++) {
          const int img = (n * 2 + grp) * 5 + (slot >> 5), kk = (2 * slot) & 63;
          uint16_t c0 = COS640[a], c1 = COS640[a >= 480 ? a - 480 : a + 160];
          if (slot == 0) c1 = COS640[(160 * d + 160 * grp) % 640];
          t.v[img][swz(np, kk)] = c0;
          t.v[img][swz(np, kk + 1)] = c1;
          a += d; if (a >= 640) a -= 640;
        }
      }
  return t;
}
__device__ const TETab g_TE = make_TE();

enum { FL_AW = 0  , FL_G = 16  , FL_H1 = 32  , FL_H2 = 48  ,
       FL_Z = 64  , FL_A0 = 224  , FL_DONE = 225, FL_X = 226  , FL_COUNT = 234 };
#define SPAD0 0
#define SPAD1 0
#define SPAD2 0
#define SPAD3 0
struct alignas(1024) Scratch {
  unsigned flags[FL_COUNT * 32 + (1024 - FL_COUNT * 32 % 1024) % 1024];
  float2 gate[2048];
  uint8_t pad0[SPAD0 * 1024 + 1024];
  uint16_t x1t[640 * 2048];
  uint8_t pad1[SPAD1 * 1024 + 1024];
  uint16_t zt[640 * 2048];
  uint8_t pad2[SPAD2 * 1024 + 1024];
  uint32_t wt[321 * 2048];
  uint8_t pad3[SPAD3 * 1024 + 1024];
  uint16_t h[2048 * 1728];
};
__device__ Scratch g_s;
#define g_X1T g_s.x1t
#define g_ZT g_s.zt
#define g_h g_s.h
#define g_WT g_s.wt
#define g_gate g_s.gate
#define g_flags g_s.flags

struct Params {
  CUtensorMap x;
  CUtensorMap wg, wu;
  CUtensorMap wgh, wuh;
  CUtensorMap tA;
  CUtensorMap x1st;
  CUtensorMap x1ld;
  CUtensorMap x1ld2;
  CUtensorMap zst32;
  CUtensorMap zst64;
  CUtensorMap zld;
  CUtensorMap hst;
  CUtensorMap hld;
  CUtensorMap wd;
  CUtensorMap wd32;
  CUtensorMap wr2, wi2;
  const uint16_t* xp;
  const uint16_t* gw;
  const uint16_t* wdp;
  const uint16_t* TEp;
  const CConst* Cp;
  uint16_t* outp;
};

#define TIMEOUT(code) do {} while (0)
#define LIM_MBAR (1 << 17)
#define LIM_FLAG (1 << 15)
#define LIM_PROG (1 << 22)
__device__ __forceinline__ uint32_t smem_u32(const void* p) { return (uint32_t)__cvta_generic_to_shared(p); }
__device__ __forceinline__ void mbar_init(uint32_t bar, uint32_t cnt) { asm volatile("mbarrier.init.shared::cta.b64 [%0], %1;" :: "r"(bar), "r"(cnt) : "memory"); }
__device__ __forceinline__ void mbar_expect_tx(uint32_t bar, uint32_t bytes) { asm volatile("mbarrier.arrive.expect_tx.shared::cta.b64 _, [%0], %1;" :: "r"(bar), "r"(bytes) : "memory"); }
__device__ __forceinline__ void mbar_arrive(uint32_t bar) { asm volatile("mbarrier.arrive.shared::cta.b64 _, [%0];" :: "r"(bar) : "memory"); }
__device__ __forceinline__ uint32_t mapa(uint32_t addr, uint32_t cta) { uint32_t r; asm volatile("mapa.shared::cluster.u32 %0, %1, %2;" : "=r"(r) : "r"(addr), "r"(cta)); return r; }
__device__ __forceinline__ void mbar_arrive_cluster(uint32_t remote_bar) { asm volatile("mbarrier.arrive.release.cluster.shared::cluster.b64 _, [%0];" :: "r"(remote_bar) : "memory"); }
__device__ __forceinline__ void mbar_wait(uint32_t bar, uint32_t parity) {
  uint32_t ok;
  int it = 0;
  do {
    asm volatile("{\n.reg .pred p;\nmbarrier.try_wait.parity.shared::cta.b64 p, [%1], %2;\nselp.u32 %0, 1, 0, p;\n}" : "=r"(ok) : "r"(bar), "r"(parity) : "memory");
    if (++it > LIM_MBAR) { TIMEOUT(bar & 0xfff); break; }
  } while (!ok);
}
__device__ __forceinline__ void mbar_wait_cluster(uint32_t bar, uint32_t parity) {
  uint32_t ok;
  int it = 0;
  do {
    asm volatile("{\n.reg .pred p;\nmbarrier.try_wait.parity.shared::cta.b64 p, [%1], %2;\nselp.u32 %0, 1, 0, p;\n}" : "=r"(ok) : "r"(bar), "r"(parity) : "memory");
    if (++it > LIM_MBAR) { TIMEOUT(bar & 0xfff); break; }
  } while (!ok);
}
__device__ __forceinline__ void tma2d(uint32_t dst, const CUtensorMap* tm, int c0, int c1, uint32_t bar) {
  asm volatile("cp.async.bulk.tensor.2d.shared::cluster.global.mbarrier::complete_tx::bytes [%0], [%1, {%3, %4}], [%2];"
    :: "r"(dst), "l"(tm), "r"(bar), "r"(c0), "r"(c1) : "memory");
}
__device__ __forceinline__ void tma3d(uint32_t dst, const CUtensorMap* tm, int c0, int c1, int c2, uint32_t bar) {
  asm volatile("cp.async.bulk.tensor.3d.shared::cluster.global.mbarrier::complete_tx::bytes [%0], [%1, {%3, %4, %5}], [%2];"
    :: "r"(dst), "l"(tm), "r"(bar), "r"(c0), "r"(c1), "r"(c2) : "memory");
}
__device__ __forceinline__ void bulk_ld(uint32_t dst, const void* src, uint32_t bytes, uint32_t bar) {
  asm volatile("cp.async.bulk.shared::cluster.global.mbarrier::complete_tx::bytes [%0], [%1], %2, [%3];"
    :: "r"(dst), "l"(src), "r"(bytes), "r"(bar) : "memory");
}
__device__ __forceinline__ void tma_st2d(const CUtensorMap* tm, uint32_t src, int c0, int c1) {
  asm volatile("cp.async.bulk.tensor.2d.global.shared::cta.bulk_group [%0, {%2, %3}], [%1];"
    :: "l"(tm), "r"(src), "r"(c0), "r"(c1) : "memory");
}
__device__ __forceinline__ void bulk_commit() { asm volatile("cp.async.bulk.commit_group;" ::: "memory"); }
__device__ __forceinline__ void bulk_wait_read() { asm volatile("cp.async.bulk.wait_group.read 0;" ::: "memory"); }
__device__ __forceinline__ void bulk_wait_all() { asm volatile("cp.async.bulk.wait_group 0;" ::: "memory"); }
__device__ __forceinline__ void l2_prefetch(const void* p, uint32_t bytes) { asm volatile("cp.async.bulk.prefetch.L2.global [%0], %1;" :: "l"(p), "r"(bytes) : "memory"); }
__device__ __forceinline__ void tmap_prefetch(const CUtensorMap* tm) { asm volatile("prefetch.tensormap [%0];" :: "l"(tm) : "memory"); }
__device__ __forceinline__ void fence_async_smem() { asm volatile("fence.proxy.async.shared::cta;" ::: "memory"); }
__device__ __forceinline__ void fence_async_all() { asm volatile("fence.proxy.async;" ::: "memory"); }
__device__ __forceinline__ void wg_fence() { asm volatile("wgmma.fence.sync.aligned;" ::: "memory"); }
__device__ __forceinline__ void wg_commit() { asm volatile("wgmma.commit_group.sync.aligned;" ::: "memory"); }
template <int N> __device__ __forceinline__ void wg_wait() { asm volatile("wgmma.wait_group.sync.aligned %0;" :: "n"(N) : "memory"); }
template <int R> __device__ __forceinline__ void reg_inc() { asm volatile("setmaxnreg.inc.sync.aligned.u32 %0;" :: "n"(R)); }
template <int R> __device__ __forceinline__ void reg_dec() { asm volatile("setmaxnreg.dec.sync.aligned.u32 %0;" :: "n"(R)); }
__device__ __forceinline__ void named_sync(int id, int n) { asm volatile("bar.sync %0, %1;" :: "r"(id), "r"(n) : "memory"); }
__device__ __forceinline__ void turn_wait(int w) { asm volatile("bar.sync %0, 256;" :: "r"(7 + w) : "memory"); }
__device__ __forceinline__ void turn_pass(int w) { asm volatile("bar.arrive %0, 256;" :: "r"(8 - w) : "memory"); }
__device__ __forceinline__ void flag_add(int f, unsigned v) { asm volatile("red.release.gpu.global.add.u32 [%0], %1;" :: "l"(&g_flags[f * 32]), "r"(v) : "memory"); }
__device__ __forceinline__ void flag_add_relaxed(int f, unsigned v) { asm volatile("red.relaxed.gpu.global.add.u32 [%0], %1;" :: "l"(&g_flags[f * 32]), "r"(v) : "memory"); }
__device__ __forceinline__ void prog_wait(uint32_t a, uint32_t target) {
  uint32_t v;
  int it = 0;
  do {
    asm volatile("ld.volatile.shared.u32 %0, [%1];" : "=r"(v) : "r"(a) : "memory");
    if (++it > LIM_PROG) { TIMEOUT(0x20000 + target); break; }
  } while (v < target);
}
__device__ __forceinline__ void stsm4(uint32_t addr, uint32_t r0, uint32_t r1, uint32_t r2, uint32_t r3) {
  asm volatile("stmatrix.sync.aligned.m8n8.x4.shared.b16 [%0], {%1, %2, %3, %4};" :: "r"(addr), "r"(r0), "r"(r1), "r"(r2), "r"(r3) : "memory");
}
__device__ __forceinline__ uint32_t pack2(float lo, float hi) { uint32_t r; asm("cvt.rn.bf16x2.f32 %0, %1, %2;" : "=r"(r) : "f"(hi), "f"(lo)); return r; }
__device__ __forceinline__ uint32_t pack2_relu(float lo, float hi) { uint32_t r; asm("cvt.rn.relu.bf16x2.f32 %0, %1, %2;" : "=r"(r) : "f"(hi), "f"(lo)); return r; }
__device__ __forceinline__ uint32_t hneg2(uint32_t a) { return a ^ 0x80008000u; }
__device__ __forceinline__ uint32_t hmul2(uint32_t a, uint32_t b) { uint32_t r; asm("mul.rn.bf16x2 %0, %1, %2;" : "=r"(r) : "r"(a), "r"(b)); return r; }
__device__ __forceinline__ uint32_t hfma2(uint32_t a, uint32_t b, uint32_t c) { uint32_t r; asm("fma.rn.bf16x2 %0, %1, %2, %3;" : "=r"(r) : "r"(a), "r"(b), "r"(c)); return r; }
__device__ __forceinline__ uint32_t reglu2(float g0, float g1, float u0, float u1) { return hmul2(pack2_relu(g0, g1), pack2(u0, u1)); }
__device__ __forceinline__ float bf_lo(uint32_t v) { return __uint_as_float(v << 16); }
__device__ __forceinline__ float bf_hi(uint32_t v) { return __uint_as_float(v & 0xffff0000u); }
__device__ __forceinline__ uint4 lds128(uint32_t a) { uint4 v; asm volatile("ld.shared.v4.u32 {%0, %1, %2, %3}, [%4];" : "=r"(v.x), "=r"(v.y), "=r"(v.z), "=r"(v.w) : "r"(a) : "memory"); return v; }
__device__ __forceinline__ float lds32f(uint32_t a) { float v; asm volatile("ld.shared.f32 %0, [%1];" : "=f"(v) : "r"(a) : "memory"); return v; }
__host__ __device__ constexpr uint64_t desc_hi(uint32_t lbo, uint32_t sbo) { return ((uint64_t)(lbo >> 4) << 16) | ((uint64_t)(sbo >> 4) << 32) | (1ull << 62); }
__device__ __forceinline__ uint32_t a16(uint32_t addr) { return (addr & 0x3FFFF) >> 4; }
__device__ __forceinline__ uint64_t dsc(uint32_t a4, uint32_t off, uint64_t hi) {
  return (hi & 0xffffffff00000000ull) | (uint64_t)(a4 + (off >> 4) + (uint32_t)hi);
}
template <int N> __device__ __forceinline__ void zero_regs(float (&d)[N]) {
#pragma unroll
  for (int i = 0; i < N; i++) d[i] = 0.f;
}
template <int N> __device__ __forceinline__ void undef_regs(float (&d)[N]) {
#pragma unroll
  for (int i = 0; i < N; i++) asm volatile("" : "=f"(d[i]));
}
template <int N> __device__ __forceinline__ void fence_regs(float (&d)[N]) {
#pragma unroll
  for (int i = 0; i < N; i++) asm volatile("" : "+f"(d[i]) :: "memory");
}

template<int TB, int SA, int OFF = 0, int N> __device__ __forceinline__ void wgmma_n64_rs(float (&d)[N], uint32_t a0, uint32_t a1, uint32_t a2, uint32_t a3, uint64_t db, int scale_d) {
  asm volatile("{\n.reg .pred p;\nsetp.ne.b32 p, %37, 0;\n"
    "wgmma.mma_async.sync.aligned.m64n64k16.f32.bf16.bf16 "
    "{%0, %1, %2, %3, %4, %5, %6, %7, %8, %9, %10, %11, %12, %13, %14, %15, "
    "%16, %17, %18, %19, %20, %21, %22, %23, %24, %25, %26, %27, %28, %29, %30, %31}, "
    "{%32, %33, %34, %35}, %36, p, %39, 1, %38;\n}\n"
    : "+f"(d[OFF + 0]), "+f"(d[OFF + 1]), "+f"(d[OFF + 2]), "+f"(d[OFF + 3]), "+f"(d[OFF + 4]), "+f"(d[OFF + 5]), "+f"(d[OFF + 6]), "+f"(d[OFF + 7]),
      "+f"(d[OFF + 8]), "+f"(d[OFF + 9]), "+f"(d[OFF + 10]), "+f"(d[OFF + 11]), "+f"(d[OFF + 12]), "+f"(d[OFF + 13]), "+f"(d[OFF + 14]), "+f"(d[OFF + 15]),
      "+f"(d[OFF + 16]), "+f"(d[OFF + 17]), "+f"(d[OFF + 18]), "+f"(d[OFF + 19]), "+f"(d[OFF + 20]), "+f"(d[OFF + 21]), "+f"(d[OFF + 22]), "+f"(d[OFF + 23]),
      "+f"(d[OFF + 24]), "+f"(d[OFF + 25]), "+f"(d[OFF + 26]), "+f"(d[OFF + 27]), "+f"(d[OFF + 28]), "+f"(d[OFF + 29]), "+f"(d[OFF + 30]), "+f"(d[OFF + 31])
    : "r"(a0), "r"(a1), "r"(a2), "r"(a3), "l"(db), "r"(scale_d), "n"(TB), "n"(SA));
}
template<int TA, int TB, int OFF = 0, int N> __device__ __forceinline__ void wgmma_n80_ss(float (&d)[N], uint64_t da, uint64_t db, int scale_d) {
  asm volatile("{\n.reg .pred p;\nsetp.ne.b32 p, %42, 0;\n"
    "wgmma.mma_async.sync.aligned.m64n80k16.f32.bf16.bf16 "
    "{%0, %1, %2, %3, %4, %5, %6, %7, %8, %9, %10, %11, %12, %13, %14, %15, "
    "%16, %17, %18, %19, %20, %21, %22, %23, %24, %25, %26, %27, %28, %29, %30, %31, "
    "%32, %33, %34, %35, %36, %37, %38, %39}, "
    "%40, %41, p, 1, 1, %43, %44;\n}\n"
    : "+f"(d[OFF + 0]), "+f"(d[OFF + 1]), "+f"(d[OFF + 2]), "+f"(d[OFF + 3]), "+f"(d[OFF + 4]), "+f"(d[OFF + 5]), "+f"(d[OFF + 6]), "+f"(d[OFF + 7]),
      "+f"(d[OFF + 8]), "+f"(d[OFF + 9]), "+f"(d[OFF + 10]), "+f"(d[OFF + 11]), "+f"(d[OFF + 12]), "+f"(d[OFF + 13]), "+f"(d[OFF + 14]), "+f"(d[OFF + 15]),
      "+f"(d[OFF + 16]), "+f"(d[OFF + 17]), "+f"(d[OFF + 18]), "+f"(d[OFF + 19]), "+f"(d[OFF + 20]), "+f"(d[OFF + 21]), "+f"(d[OFF + 22]), "+f"(d[OFF + 23]),
      "+f"(d[OFF + 24]), "+f"(d[OFF + 25]), "+f"(d[OFF + 26]), "+f"(d[OFF + 27]), "+f"(d[OFF + 28]), "+f"(d[OFF + 29]), "+f"(d[OFF + 30]), "+f"(d[OFF + 31]),
      "+f"(d[OFF + 32]), "+f"(d[OFF + 33]), "+f"(d[OFF + 34]), "+f"(d[OFF + 35]), "+f"(d[OFF + 36]), "+f"(d[OFF + 37]), "+f"(d[OFF + 38]), "+f"(d[OFF + 39])
    : "l"(da), "l"(db), "r"(scale_d), "n"(TA), "n"(TB));
}
template<int TA, int TB, int OFF = 0, int N> __device__ __forceinline__ void wgmma_n128_ss(float (&d)[N], uint64_t da, uint64_t db, int scale_d) {
  asm volatile("{\n.reg .pred p;\nsetp.ne.b32 p, %66, 0;\n"
    "wgmma.mma_async.sync.aligned.m64n128k16.f32.bf16.bf16 "
    "{%0, %1, %2, %3, %4, %5, %6, %7, %8, %9, %10, %11, %12, %13, %14, %15, "
    "%16, %17, %18, %19, %20, %21, %22, %23, %24, %25, %26, %27, %28, %29, %30, %31, "
    "%32, %33, %34, %35, %36, %37, %38, %39, %40, %41, %42, %43, %44, %45, %46, %47, "
    "%48, %49, %50, %51, %52, %53, %54, %55, %56, %57, %58, %59, %60, %61, %62, %63}, "
    "%64, %65, p, 1, 1, %67, %68;\n}\n"
    : "+f"(d[OFF + 0]), "+f"(d[OFF + 1]), "+f"(d[OFF + 2]), "+f"(d[OFF + 3]), "+f"(d[OFF + 4]), "+f"(d[OFF + 5]), "+f"(d[OFF + 6]), "+f"(d[OFF + 7]),
      "+f"(d[OFF + 8]), "+f"(d[OFF + 9]), "+f"(d[OFF + 10]), "+f"(d[OFF + 11]), "+f"(d[OFF + 12]), "+f"(d[OFF + 13]), "+f"(d[OFF + 14]), "+f"(d[OFF + 15]),
      "+f"(d[OFF + 16]), "+f"(d[OFF + 17]), "+f"(d[OFF + 18]), "+f"(d[OFF + 19]), "+f"(d[OFF + 20]), "+f"(d[OFF + 21]), "+f"(d[OFF + 22]), "+f"(d[OFF + 23]),
      "+f"(d[OFF + 24]), "+f"(d[OFF + 25]), "+f"(d[OFF + 26]), "+f"(d[OFF + 27]), "+f"(d[OFF + 28]), "+f"(d[OFF + 29]), "+f"(d[OFF + 30]), "+f"(d[OFF + 31]),
      "+f"(d[OFF + 32]), "+f"(d[OFF + 33]), "+f"(d[OFF + 34]), "+f"(d[OFF + 35]), "+f"(d[OFF + 36]), "+f"(d[OFF + 37]), "+f"(d[OFF + 38]), "+f"(d[OFF + 39]),
      "+f"(d[OFF + 40]), "+f"(d[OFF + 41]), "+f"(d[OFF + 42]), "+f"(d[OFF + 43]), "+f"(d[OFF + 44]), "+f"(d[OFF + 45]), "+f"(d[OFF + 46]), "+f"(d[OFF + 47]),
      "+f"(d[OFF + 48]), "+f"(d[OFF + 49]), "+f"(d[OFF + 50]), "+f"(d[OFF + 51]), "+f"(d[OFF + 52]), "+f"(d[OFF + 53]), "+f"(d[OFF + 54]), "+f"(d[OFF + 55]),
      "+f"(d[OFF + 56]), "+f"(d[OFF + 57]), "+f"(d[OFF + 58]), "+f"(d[OFF + 59]), "+f"(d[OFF + 60]), "+f"(d[OFF + 61]), "+f"(d[OFF + 62]), "+f"(d[OFF + 63])
    : "l"(da), "l"(db), "r"(scale_d), "n"(TA), "n"(TB));
}
template<int TA, int TB, int OFF = 0, int N> __device__ __forceinline__ void wgmma_n160_ss(float (&d)[N], uint64_t da, uint64_t db, int scale_d) {
  asm volatile("{\n.reg .pred p;\nsetp.ne.b32 p, %82, 0;\n"
    "wgmma.mma_async.sync.aligned.m64n160k16.f32.bf16.bf16 "
    "{%0, %1, %2, %3, %4, %5, %6, %7, %8, %9, %10, %11, %12, %13, %14, %15, "
    "%16, %17, %18, %19, %20, %21, %22, %23, %24, %25, %26, %27, %28, %29, %30, %31, "
    "%32, %33, %34, %35, %36, %37, %38, %39, %40, %41, %42, %43, %44, %45, %46, %47, "
    "%48, %49, %50, %51, %52, %53, %54, %55, %56, %57, %58, %59, %60, %61, %62, %63, "
    "%64, %65, %66, %67, %68, %69, %70, %71, %72, %73, %74, %75, %76, %77, %78, %79}, "
    "%80, %81, p, 1, 1, %83, %84;\n}\n"
    : "+f"(d[OFF + 0]), "+f"(d[OFF + 1]), "+f"(d[OFF + 2]), "+f"(d[OFF + 3]), "+f"(d[OFF + 4]), "+f"(d[OFF + 5]), "+f"(d[OFF + 6]), "+f"(d[OFF + 7]),
      "+f"(d[OFF + 8]), "+f"(d[OFF + 9]), "+f"(d[OFF + 10]), "+f"(d[OFF + 11]), "+f"(d[OFF + 12]), "+f"(d[OFF + 13]), "+f"(d[OFF + 14]), "+f"(d[OFF + 15]),
      "+f"(d[OFF + 16]), "+f"(d[OFF + 17]), "+f"(d[OFF + 18]), "+f"(d[OFF + 19]), "+f"(d[OFF + 20]), "+f"(d[OFF + 21]), "+f"(d[OFF + 22]), "+f"(d[OFF + 23]),
      "+f"(d[OFF + 24]), "+f"(d[OFF + 25]), "+f"(d[OFF + 26]), "+f"(d[OFF + 27]), "+f"(d[OFF + 28]), "+f"(d[OFF + 29]), "+f"(d[OFF + 30]), "+f"(d[OFF + 31]),
      "+f"(d[OFF + 32]), "+f"(d[OFF + 33]), "+f"(d[OFF + 34]), "+f"(d[OFF + 35]), "+f"(d[OFF + 36]), "+f"(d[OFF + 37]), "+f"(d[OFF + 38]), "+f"(d[OFF + 39]),
      "+f"(d[OFF + 40]), "+f"(d[OFF + 41]), "+f"(d[OFF + 42]), "+f"(d[OFF + 43]), "+f"(d[OFF + 44]), "+f"(d[OFF + 45]), "+f"(d[OFF + 46]), "+f"(d[OFF + 47]),
      "+f"(d[OFF + 48]), "+f"(d[OFF + 49]), "+f"(d[OFF + 50]), "+f"(d[OFF + 51]), "+f"(d[OFF + 52]), "+f"(d[OFF + 53]), "+f"(d[OFF + 54]), "+f"(d[OFF + 55]),
      "+f"(d[OFF + 56]), "+f"(d[OFF + 57]), "+f"(d[OFF + 58]), "+f"(d[OFF + 59]), "+f"(d[OFF + 60]), "+f"(d[OFF + 61]), "+f"(d[OFF + 62]), "+f"(d[OFF + 63]),
      "+f"(d[OFF + 64]), "+f"(d[OFF + 65]), "+f"(d[OFF + 66]), "+f"(d[OFF + 67]), "+f"(d[OFF + 68]), "+f"(d[OFF + 69]), "+f"(d[OFF + 70]), "+f"(d[OFF + 71]),
      "+f"(d[OFF + 72]), "+f"(d[OFF + 73]), "+f"(d[OFF + 74]), "+f"(d[OFF + 75]), "+f"(d[OFF + 76]), "+f"(d[OFF + 77]), "+f"(d[OFF + 78]), "+f"(d[OFF + 79])
    : "l"(da), "l"(db), "r"(scale_d), "n"(TA), "n"(TB));
}
template<int TA, int TB, int OFF = 0, int N> __device__ __forceinline__ void wgmma_n256_ss(float (&d)[N], uint64_t da, uint64_t db, int scale_d) {
  asm volatile("{\n.reg .pred p;\nsetp.ne.b32 p, %130, 0;\n"
    "wgmma.mma_async.sync.aligned.m64n256k16.f32.bf16.bf16 "
    "{%0, %1, %2, %3, %4, %5, %6, %7, %8, %9, %10, %11, %12, %13, %14, %15, "
    "%16, %17, %18, %19, %20, %21, %22, %23, %24, %25, %26, %27, %28, %29, %30, %31, "
    "%32, %33, %34, %35, %36, %37, %38, %39, %40, %41, %42, %43, %44, %45, %46, %47, "
    "%48, %49, %50, %51, %52, %53, %54, %55, %56, %57, %58, %59, %60, %61, %62, %63, "
    "%64, %65, %66, %67, %68, %69, %70, %71, %72, %73, %74, %75, %76, %77, %78, %79, "
    "%80, %81, %82, %83, %84, %85, %86, %87, %88, %89, %90, %91, %92, %93, %94, %95, "
    "%96, %97, %98, %99, %100, %101, %102, %103, %104, %105, %106, %107, %108, %109, %110, %111, "
    "%112, %113, %114, %115, %116, %117, %118, %119, %120, %121, %122, %123, %124, %125, %126, %127}, "
    "%128, %129, p, 1, 1, %131, %132;\n}\n"
    : "+f"(d[OFF + 0]), "+f"(d[OFF + 1]), "+f"(d[OFF + 2]), "+f"(d[OFF + 3]), "+f"(d[OFF + 4]), "+f"(d[OFF + 5]), "+f"(d[OFF + 6]), "+f"(d[OFF + 7]),
      "+f"(d[OFF + 8]), "+f"(d[OFF + 9]), "+f"(d[OFF + 10]), "+f"(d[OFF + 11]), "+f"(d[OFF + 12]), "+f"(d[OFF + 13]), "+f"(d[OFF + 14]), "+f"(d[OFF + 15]),
      "+f"(d[OFF + 16]), "+f"(d[OFF + 17]), "+f"(d[OFF + 18]), "+f"(d[OFF + 19]), "+f"(d[OFF + 20]), "+f"(d[OFF + 21]), "+f"(d[OFF + 22]), "+f"(d[OFF + 23]),
      "+f"(d[OFF + 24]), "+f"(d[OFF + 25]), "+f"(d[OFF + 26]), "+f"(d[OFF + 27]), "+f"(d[OFF + 28]), "+f"(d[OFF + 29]), "+f"(d[OFF + 30]), "+f"(d[OFF + 31]),
      "+f"(d[OFF + 32]), "+f"(d[OFF + 33]), "+f"(d[OFF + 34]), "+f"(d[OFF + 35]), "+f"(d[OFF + 36]), "+f"(d[OFF + 37]), "+f"(d[OFF + 38]), "+f"(d[OFF + 39]),
      "+f"(d[OFF + 40]), "+f"(d[OFF + 41]), "+f"(d[OFF + 42]), "+f"(d[OFF + 43]), "+f"(d[OFF + 44]), "+f"(d[OFF + 45]), "+f"(d[OFF + 46]), "+f"(d[OFF + 47]),
      "+f"(d[OFF + 48]), "+f"(d[OFF + 49]), "+f"(d[OFF + 50]), "+f"(d[OFF + 51]), "+f"(d[OFF + 52]), "+f"(d[OFF + 53]), "+f"(d[OFF + 54]), "+f"(d[OFF + 55]),
      "+f"(d[OFF + 56]), "+f"(d[OFF + 57]), "+f"(d[OFF + 58]), "+f"(d[OFF + 59]), "+f"(d[OFF + 60]), "+f"(d[OFF + 61]), "+f"(d[OFF + 62]), "+f"(d[OFF + 63]),
      "+f"(d[OFF + 64]), "+f"(d[OFF + 65]), "+f"(d[OFF + 66]), "+f"(d[OFF + 67]), "+f"(d[OFF + 68]), "+f"(d[OFF + 69]), "+f"(d[OFF + 70]), "+f"(d[OFF + 71]),
      "+f"(d[OFF + 72]), "+f"(d[OFF + 73]), "+f"(d[OFF + 74]), "+f"(d[OFF + 75]), "+f"(d[OFF + 76]), "+f"(d[OFF + 77]), "+f"(d[OFF + 78]), "+f"(d[OFF + 79]),
      "+f"(d[OFF + 80]), "+f"(d[OFF + 81]), "+f"(d[OFF + 82]), "+f"(d[OFF + 83]), "+f"(d[OFF + 84]), "+f"(d[OFF + 85]), "+f"(d[OFF + 86]), "+f"(d[OFF + 87]),
      "+f"(d[OFF + 88]), "+f"(d[OFF + 89]), "+f"(d[OFF + 90]), "+f"(d[OFF + 91]), "+f"(d[OFF + 92]), "+f"(d[OFF + 93]), "+f"(d[OFF + 94]), "+f"(d[OFF + 95]),
      "+f"(d[OFF + 96]), "+f"(d[OFF + 97]), "+f"(d[OFF + 98]), "+f"(d[OFF + 99]), "+f"(d[OFF + 100]), "+f"(d[OFF + 101]), "+f"(d[OFF + 102]), "+f"(d[OFF + 103]),
      "+f"(d[OFF + 104]), "+f"(d[OFF + 105]), "+f"(d[OFF + 106]), "+f"(d[OFF + 107]), "+f"(d[OFF + 108]), "+f"(d[OFF + 109]), "+f"(d[OFF + 110]), "+f"(d[OFF + 111]),
      "+f"(d[OFF + 112]), "+f"(d[OFF + 113]), "+f"(d[OFF + 114]), "+f"(d[OFF + 115]), "+f"(d[OFF + 116]), "+f"(d[OFF + 117]), "+f"(d[OFF + 118]), "+f"(d[OFF + 119]),
      "+f"(d[OFF + 120]), "+f"(d[OFF + 121]), "+f"(d[OFF + 122]), "+f"(d[OFF + 123]), "+f"(d[OFF + 124]), "+f"(d[OFF + 125]), "+f"(d[OFF + 126]), "+f"(d[OFF + 127])
    : "l"(da), "l"(db), "r"(scale_d), "n"(TA), "n"(TB));
}

enum { IT_FFN = 0, IT_HALF = 1, IT_DFT = 2, IT_NONE = 3 };
#define LAG 2
#define LAG_DFT 3
#define LAGS 2
#define LAGS_Q 1
#define XEARLY 1
#define LAGE 3
__device__ __forceinline__ int get_item(int b, int i, int& u, int& v) {
  const int r = b & 1, p = (b >> 1) & 3, q = b >> 3;
  if (i == 0) {
    if (q >= 16) { u = b - 116; v = 5; return IT_FFN; }
    if (q < 10) { u = 4 * (q < 8 ? q & 3 : q - 8) + 2 * (p & 1) + r; v = 2 * (q < 8 ? q >> 2 : 2) + (p >> 1); return IT_FFN; }
    if (q == 10) { u = 8 + 2 * p + r; v = 4; return IT_FFN; }
    if (q < 15) { u = 2 * (p & 1) + r; v = 2 * (q - 11) + (p >> 1); return IT_DFT; }
    u = 4; v = 2 * p + r; return IT_DFT;
  }
  if (b >= 124) return IT_NONE;
  if (q >= 8 && q <= 10) {
    const int pp = 4 * (q - 8) + p, a = pp / 3, k = pp - 3 * a;
    if (k == 2) { u = 4 * a + 2 * r; v = 13; return IT_HALF; }
    u = 4 * a + 2 * k + r; v = 12; return IT_FFN;
  }
  if (q == 15) { u = 8 + 2 * p + r; v = 5; return IT_FFN; }
  u = 4 * (q < 8 ? q & 3 : q - 11) + 2 * (p & 1) + r;
  v = 2 * (q < 8 ? 3 + (q >> 2) : 5) + (p >> 1);
  return IT_FFN;
}
__device__ __forceinline__ int n_gemm1(int b) { return b >= 124 ? 1 : 2; }
__device__ __forceinline__ int n_chain(int b) { return b < 124 ? (b & 1) * 2 : b < 128 ? 4 : (b < 130 ? 6 : b == 130 ? 5 : 4); }
__device__ __forceinline__ int chain_id(int b, int j) {
  if (b < 124) return (b & ~1) + j;
  if (j < 2) return 129 + 2 * (b - 124) + j;
  if (b < 128) { const int i = 2 * (b - 124) + (j & 1); return i < 5 ? 124 + i : 140 + i; }
  return 148 + 8 * ((j >> 1) - 1) + 2 * (b - 128) + (j & 1);
}
__device__ __forceinline__ int chain_ka(int c) { return c == 0 ? 0 : c == 1 ? 160 : c - 1; }
__device__ __forceinline__ int chain_kb(int c) { return c == 0 ? 320 : c == 1 ? 160 : 321 - c; }
__device__ __forceinline__ void out_tile(int b, int& m, int& n) {
  const int q = (b >> 3) & 15, p = (b >> 1) & 3;
  const int np_ = q < 8 ? (q & 1) : ((q + 1) & 1);
  const int mp = q < 8 ? (q >> 1) : 4 + ((q - 8) >> 1);
  m = 2 * mp + (p >> 1); n = 2 * np_ + (p & 1);
}
#define HP 7
__device__ __forceinline__ int ffn_kb(int rank, int np, int i) {
  if (rank == 0) return i < HP ? i : i + 10 - HP;
  return i < 10 - HP ? HP + i : i + np;
}
template <bool SMAP> __device__ __forceinline__ int virtual_id() {
  if (SMAP) {
    uint32_t smid;
    asm volatile("mov.u32 %0, %%smid;" : "=r"(smid));
    const int t = smid >> 1;
    int vc;
    if (t < 32) vc = 4 * (t & 7) + (t >> 3);
    else if (t < 60) vc = 4 * (8 + (t - 32) % 7) + (t - 32) / 7;
    else vc = t < 62 ? t + 4 : t - 2;
    return 2 * vc + (smid & 1);
  }
  return blockIdx.x;
}
#define NP_REG 18
#define NP_EC 14
__device__ __forceinline__ int n_ffn_p(int b) { return b < 124 ? NP_REG : NP_EC; }

struct Ring {
  uint32_t ord, phm, i;
  __device__ __forceinline__ uint32_t slot() const { return (ord >> ((i & 3) * 2)) & 3; }
  __device__ __forceinline__ uint32_t par(uint32_t s) const { return (phm >> s) & 1; }
  __device__ __forceinline__ void next(uint32_t s) { phm ^= 1u << s; i++; }
  __device__ __forceinline__ uint32_t islot(uint32_t c, int j) const { return (c + 1 + (j >= 3 ? j - 3 : j)) & 3; }
  __device__ __forceinline__ uint32_t ipar(uint32_t c, int j) const { return par(islot(c, j)) ^ (j >= 3); }
  __device__ __forceinline__ void after_fft(uint32_t c, int n) {
    const int r = n >= 6 ? n - 6 : n >= 3 ? n - 3 : n;
    const uint32_t s0 = (c + 1 + r) & 3, s1 = (c + 1 + (r == 2 ? 0 : r + 1)) & 3, s2 = (c + 1 + (r == 0 ? 2 : r - 1)) & 3;
    phm ^= 1u << c;
    if (((n + 2) / 3) & 1) phm ^= 1u << ((c + 1) & 3);
    if (((n + 1) / 3) & 1) phm ^= 1u << ((c + 2) & 3);
    if ((n / 3) & 1) phm ^= 1u << ((c + 3) & 3);
    ord = s0 | (s1 << 2) | (s2 << 4) | (c << 6);
    i = 0;
  }
};
__device__ __forceinline__ uint32_t e_addr_y(const uint32_t (&s)[3], int i, int sh = 0) {
  return i == 0 ? s[0] : i == 1 ? s[0] + (26624 >> sh) : i == 2 ? s[1] + (10240 >> sh) : i == 3 ? s[2] : s[2] + (16384 >> sh);
}
__device__ __forceinline__ uint32_t e_addr_t(const uint32_t (&s)[3], int i, int sh = 0) {
  return i == 0 ? s[0] + (16384 >> sh) : i == 1 ? s[1] : i == 2 ? s[1] + (26624 >> sh) : i == 3 ? s[1] + (36864 >> sh) : s[2] + (32768 >> sh);
}
__device__ __forceinline__ bool seg_wait(int k, int n, int ls, int le) { return !(k > 0 && k < ls) && !(k > n - le); }
__device__ __forceinline__ bool seg_pass(int k, int n, int ls, int le) { return !(k < ls - 1) && !(k >= n - le && k < n - 1); }

#define ER_FROM0 0
#define ER_FROM1 0
#define ER_FROMD 0
#define RELEASE_SLOT(drain) do { \
    if (drain) { wg_wait<0>(); if (t128 == 0) { if (pend) mbar_arrive(bar_empty + 8 * prev); mbar_arrive(bar_empty + 8 * sl); } pend = false; } \
    else { if (pend) { wg_wait<1>(); if (t128 == 0) mbar_arrive(bar_empty + 8 * prev); } pend = true; } } while (0)
#define RELEASE_LAST() do { if (pend && t128 == 0) mbar_arrive(bar_empty + 8 * prev); } while (0)
#define STF_COUNT 4
#define STF_ARRIVE(bar) do { __syncwarp(); if (lane == 0) mbar_arrive(bar); } while (0)
__device__ __forceinline__ void wait_kb(uint32_t kbw, int kb) {
  uint32_t v;
  int it = 0;
  while (true) {
    asm volatile("ld.volatile.shared.u32 %0, [%1];" : "=r"(v) : "r"(kbw) : "memory");
    if (v > (uint32_t)kb) break;
    if (++it > LIM_PROG) { TIMEOUT(0x30000 + kb); break; }
    if (WKB_NS > 0) __nanosleep(WKB_NS);
  }
}
__device__ __forceinline__ bool mate_is_partner(uint32_t bar_mate, uint32_t matew, int b) {
  mbar_wait_cluster(bar_mate, 0);
  uint32_t v;
  asm volatile("ld.shared.u32 %0, [%1];" : "=r"(v) : "r"(matew) : "memory");
  return (int)v == (b ^ 1);
}
__device__ __forceinline__ void issue_gemm1(const Params& P, int ty, int u, int v, int kb, uint32_t a, uint32_t full) {
  mbar_expect_tx(full, STAGE_BYTES);
  if (ty == IT_DFT) {
    tma2d(a, &P.tA, kb * 64, u * 128, full);
    tma2d(a + 16384, &P.x, kb * 64, v * 256, full);
    tma2d(a + 32768, &P.x, kb * 64, v * 256 + 128, full);
  } else if (ty == IT_HALF) {
    tma2d(a, &P.x, kb * 64, u * 128, full);
    tma2d(a + 16384, &P.x, kb * 64, u * 128 + 128, full);
    tma2d(a + 32768, &P.wgh, 1664, kb * 64, full);
    tma2d(a + 40960, &P.wuh, 1664, kb * 64, full);
  } else {
    tma2d(a, &P.x, kb * 64, u * 128, full);
    tma3d(a + 16384, &P.wg, 0, kb * 64, v * 2, full);
    tma3d(a + 32768, &P.wu, 0, kb * 64, v * 2, full);
  }
}

template <bool SMAP>
__global__ void __cluster_dims__(2, 1, 1) __launch_bounds__(384, 1) fused_kernel(const __grid_constant__ Params P) {
  extern __shared__ uint8_t smem_raw[];
  const uint32_t sb = (smem_u32(smem_raw) + 1023) & ~1023u;
  const uint32_t bar_full = sb + OFF_BAR, bar_empty = bar_full + 32, bar_stf = bar_full + 64, bar_ste = bar_full + 80;
  const uint32_t bar_rx = bar_full + 96, bar_rdy = bar_full + 112, bar_gate = bar_full + 128, bar_side = bar_full + 144;
  const uint32_t bar_go = bar_full + 152, prog = bar_full + 160, bar_ef = bar_full + 176, kbw = bar_full + 216, bar_mate = bar_full + 224, matew = bar_full + 232, bar_rx2 = bar_full + 240;
  const int tid = threadIdx.x, lane = tid & 31;
  const int warp = __shfl_sync(0xffffffffu, tid >> 5, 0);
  const int b = __shfl_sync(0xffffffffu, virtual_id<SMAP>(), 0);
  const uint32_t crank = blockIdx.x & 1;
  const bool outjob = b < 128;

  if (tid == 256) {
    for (int s = 0; s < NSTAGE; s++) { mbar_init(bar_full + 8 * s, 1); mbar_init(bar_empty + 8 * s, 2); }
    asm volatile("fence.mbarrier_init.release.cluster;" ::: "memory");
    int u, v;
    const int ty = get_item(b, 0, u, v);
#pragma unroll 1
    for (int kb = 0; kb < NFIRST; kb++) issue_gemm1(P, ty, u, v, kb, sb + kb * STAGE_BYTES, bar_full + 8 * kb);
  }
  if (tid == 0) {
    for (int w = 0; w < 2; w++) {
      mbar_init(bar_stf + 8 * w, STF_COUNT); mbar_init(bar_ste + 8 * w, 1);
      mbar_init(bar_rx + 8 * w, 1); mbar_init(bar_rdy + 8 * w, 1); mbar_init(bar_gate + 8 * w, 1); mbar_init(bar_rx2 + 8 * w, 1);
    }
    mbar_init(bar_side, 1);
    mbar_init(bar_go, 2);
    mbar_init(bar_mate, 1);
    for (int s = 0; s < 5; s++) mbar_init(bar_ef + 8 * s, 1);
    asm volatile("st.shared.u32 [%0], %1;" :: "r"(prog), "r"(0) : "memory");
    asm volatile("st.shared.u32 [%0], %1;" :: "r"(kbw), "r"(0) : "memory");
    asm volatile("fence.mbarrier_init.release.cluster;" ::: "memory");
    mbar_expect_tx(bar_rx, 10240);
    mbar_expect_tx(bar_rx + 8, 10240);
    mbar_expect_tx(bar_rx2, 5120);
    mbar_expect_tx(bar_rx2 + 8, 5120);
    mbar_expect_tx(bar_mate, 4);
  }
  __syncthreads();
  asm volatile("barrier.cluster.arrive.relaxed.aligned;" ::: "memory");

  const int ng1 = n_gemm1(b), nch = n_chain(b);

  if (warp >= 8) {
    reg_dec<56>();
    if (warp == 8) {
      if (lane == 0) {
        Ring rg{0xE4, 0xF ^ ((1 << NFIRST) - 1), NFIRST};
        for (int i = 0; i < ng1; i++) {
          int u, v;
          const int ty = get_item(b, i, u, v);
          for (int kb = i == 0 ? NFIRST : 0; kb < 10; kb++) {
            const uint32_t sl = rg.slot(), full = bar_full + 8 * sl, a = sb + sl * STAGE_BYTES;
            mbar_wait(bar_empty + 8 * sl, rg.par(sl));
            issue_gemm1(P, ty, u, v, kb, a, full);
            rg.next(sl);
            if (i == 0 && kb == 5) {
              if (ng1 == 2) { tmap_prefetch(&P.wg); tmap_prefetch(&P.wu); tmap_prefetch(&P.wgh); tmap_prefetch(&P.wuh); }
              tmap_prefetch(&P.hst); tmap_prefetch(&P.x1st);
            }
            if (i == ng1 - 1 && kb == 5) {
              tmap_prefetch(&P.x1ld2); if (b == 1) tmap_prefetch(&P.x1ld); tmap_prefetch(&P.hld); tmap_prefetch(&P.wd); tmap_prefetch(&P.wd32);
              tmap_prefetch(&P.zld); tmap_prefetch(&P.zst64); tmap_prefetch(&P.zst32);
            }
          }
        }
        if (nch > 0) {
          const uint32_t c = rg.slot();
          mbar_wait(bar_empty + 8 * c, rg.par(c));
          mbar_expect_tx(bar_full + 8 * c, sizeof(CConst));
          bulk_ld(sb + c * STAGE_BYTES, P.Cp, sizeof(CConst), bar_full + 8 * c);
          prog_wait(prog, 1);
          auto load_x = [&](int ch, uint32_t ax, uint32_t full) {
            if (ch >= 2) {
              tma2d(ax, &P.x1ld2, 0, 128 * (ch - 1), full);
            } else {
              tma2d(ax, &P.x1ld, 0, 64 * ch, full);
              tma2d(ax + 8192, &P.x1ld, 0, 64 * ch, full);
            }
          };
          auto load_w = [&](int ch, uint32_t aw, uint32_t full) {
            bulk_ld(aw, g_WT + chain_ka(ch) * 2048, 8192, full);
            bulk_ld(aw + 8192, g_WT + chain_kb(ch) * 2048, 8192, full);
          };
          if (nch == 2) {
            const int ch = chain_id(b, 0);
            const uint32_t s0 = rg.islot(c, 0), f0 = bar_full + 8 * s0, a0 = sb + s0 * STAGE_BYTES;
            mbar_wait(bar_empty + 8 * s0, rg.ipar(c, 0));
            mbar_expect_tx(f0, 49152);
            load_x(ch, a0, f0);
            load_x(ch + 1, a0 + 16384, f0);
            load_w(ch, a0 + 32768, f0);
            const uint32_t s1 = rg.islot(c, 1), f1 = bar_full + 8 * s1;
            mbar_wait(bar_empty + 8 * s1, rg.ipar(c, 1));
            mbar_expect_tx(f1, 16384);
            load_w(ch + 1, sb + s1 * STAGE_BYTES, f1);
          } else
          for (int j = 0; j < nch; j++) {
            if (j == 2) prog_wait(prog, 2);
            const int ch = chain_id(b, j);
            const uint32_t sl = rg.islot(c, j), full = bar_full + 8 * sl, a = sb + sl * STAGE_BYTES;
            mbar_wait(bar_empty + 8 * sl, rg.ipar(c, j));
            mbar_expect_tx(full, 32768);
            load_x(ch, a, full);
            load_w(ch, a + 16384, full);
          }
          mbar_wait(bar_full + 8 * rg.islot(c, nch - 1), rg.ipar(c, nch - 1) ^ 1);
          rg.after_fft(c, nch);
        }
        if (outjob) {
          const int rank = b & 1;
          int m, n;
          out_tile(b, m, n);
          const int np = n_ffn_p(b), nf = rank ? 27 - np : np;
          const int wc = n * 160 + ((n & 1) ? 32 : 0), wc32 = n * 160 + ((n & 1) ? 0 : 128);
          prog_wait(prog, 2);
          for (int i = 0; i < nf; i++) {
            const int kb = ffn_kb(rank, np, i);
            if (i == (rank ? 10 - HP : HP)) prog_wait(prog, 3);
            const uint32_t sl = rg.slot(), full = bar_full + 8 * sl, a = sb + sl * STAGE_BYTES;
            mbar_wait(bar_empty + 8 * sl, rg.par(sl));
            mbar_expect_tx(full, 36864);
            tma2d(a, &P.hld, kb * 64, m * 128, full);
            tma2d(a + 16384, &P.wd, wc, kb * 64, full);
            tma2d(a + 24576, &P.wd, wc + 64, kb * 64, full);
            tma2d(a + 32768, &P.wd32, wc32, kb * 64, full);
            rg.next(sl);
          }
          {
            uint32_t es_[3];
            const uint16_t* te = P.TEp + (n * 2 + rank) * 5 * 5120;
            auto slot = [&](int k) { const uint32_t sl = rg.slot(); mbar_wait(bar_empty + 8 * sl, rg.par(sl)); es_[k] = sb + sl * STAGE_BYTES; rg.next(sl); };
            auto table = [&](int i) { mbar_expect_tx(bar_ef + 8 * i, 16384 + 10240); bulk_ld(e_addr_t(es_, i), te + i * 5120, 10240, bar_ef + 8 * i); };
            auto ytile = [&](int i) { prog_wait(prog, 4 + i); tma3d(e_addr_y(es_, i), &P.zld, 0, rank * 320 + i * 64, m * 2, bar_ef + 8 * i); };
            es_[1] = es_[2] = 0;
            slot(0); table(0); ytile(0);
            mbar_expect_tx(bar_ef + 8, 16384 + 10240); ytile(1);
            slot(1); bulk_ld(e_addr_t(es_, 1), te + 5120, 10240, bar_ef + 8);
            table(2); ytile(2); table(3);
            slot(2); ytile(3); table(4); ytile(4);
          }
        }
      }
      __syncwarp();
    } else {
      const int sw = warp - 9;
      const uint32_t wst = sb + OFF_STG;
      if (outjob) {
        if (sw < 2) {
          const int p = b & 31, ci = b >> 5;
          const int e0 = (321 * p) & ~7, mis = (321 * p) & 7;
          if (sw == 0 && lane == 0) {
            mbar_expect_tx(bar_side, 4 * 5376);
            wait_kb(kbw, WJOB_KB);
            tma2d(wst, &P.wr2, e0, 16 * ci, bar_side);
            wait_kb(kbw, WJOB_KB + WJOB_STEP);
            tma2d(wst + 5376, &P.wr2, e0 + 168, 16 * ci, bar_side);
            wait_kb(kbw, WJOB_KB + 2 * WJOB_STEP);
            tma2d(wst + 2 * 5376, &P.wi2, e0, 16 * ci, bar_side);
            wait_kb(kbw, WJOB_KB + 3 * WJOB_STEP);
            tma2d(wst + 3 * 5376, &P.wi2, e0 + 168, 16 * ci, bar_side);
          }
          mbar_wait(bar_side, 0);
          const uint32_t dst0 = ci * 512 + ((p >> 3) * 32 + (p & 7) * 4 + (lane & 3)) * 4;
          const uint32_t la = wst + (lane >> 4) * (2 * 5376) + (lane & 15) * 336;
#pragma unroll 7
          for (int jg = sw; jg < 42; jg += 2) {
            const int hb = jg >= 21;
            uint32_t r0, r1, r2, r3;
            asm volatile("ldmatrix.sync.aligned.m8n8.x4.trans.shared.b16 {%0, %1, %2, %3}, [%4];"
                         : "=r"(r0), "=r"(r1), "=r"(r2), "=r"(r3) : "r"(la + hb * 5376 + (jg - 21 * hb) * 16) : "memory");
            const int c = jg * 8 + (lane >> 2) - mis;
            const uint32_t sc = (c == 0 || c == 320) ? 0x3e803e80u : c == 160 ? 0x3f003f00u : 0x3f803f80u;
            if (sc != 0x3f803f80u) {
              asm("mul.rn.bf16x2 %0, %0, %1;" : "+r"(r0) : "r"(sc));
              asm("mul.rn.bf16x2 %0, %0, %1;" : "+r"(r1) : "r"(sc));
              asm("mul.rn.bf16x2 %0, %0, %1;" : "+r"(r2) : "r"(sc));
              asm("mul.rn.bf16x2 %0, %0, %1;" : "+r"(r3) : "r"(sc));
            }
            if (c >= 0 && c < DF_)
              *(uint4*)(g_WT + (size_t)c * 2048 + dst0) =
                  make_uint4(r0, r2, r1, r3);
          }
          __syncwarp();
          if (lane == 0) mbar_arrive(bar_go);
          fence_async_all();
          named_sync(5, 64);
          if (sw == 0) {
            if (lane < 17) flag_add(lane < 16 ? FL_AW + lane : FL_A0, 1);
          }
        }
      }
      asm volatile("barrier.cluster.wait.aligned;" ::: "memory");
      if (sw < 2) {
        const int w = sw;
        const uint32_t stg = sb + OFF_STG + w * 16384, stf = bar_stf + 8 * w, ste = bar_ste + 8 * w;
        uint32_t ph = 0;
        for (int i = 0; i < ng1; i++) {
          if (lane == 0) {
            int u, v;
            const int ty = get_item(b, i, u, v);
            if (ty == IT_DFT) {
              mbar_wait(stf, ph); ph ^= 1;
              tma_st2d(&P.x1st, stg, v * 256 + w * 128, u * 128);
              tma_st2d(&P.x1st, stg + 8192, v * 256 + w * 128 + 64, u * 128);
              bulk_commit();
              bulk_wait_read();
              mbar_arrive(ste);
              if (u == 4) { bulk_wait_all(); flag_add_relaxed(FL_A0, 1); }
              mbar_wait(stf, ph); ph ^= 1;
              tma_st2d(&P.x1st, stg, v * 256 + w * 128, u * 128 + 64);
              tma_st2d(&P.x1st, stg + 8192, v * 256 + w * 128 + 64, u * 128 + 64);
            } else {
              mbar_wait(stf, ph); ph ^= 1;
              if (i == 0 && STORE_DELAY > 0) {
                const unsigned c0 = clock();
                for (int it = 0; it < 64 && clock() - c0 < STORE_DELAY; it++) __nanosleep(64);
              }
              if (ty == IT_FFN) {
                tma_st2d(&P.hst, stg, v * 128, u * 128 + w * 64);
                tma_st2d(&P.hst, stg + 8192, v * 128 + 64, u * 128 + w * 64);
              } else {
                tma_st2d(&P.hst, stg, 1664, (u + w) * 128);
                tma_st2d(&P.hst, stg + 8192, 1664, (u + w) * 128 + 64);
              }
            }
            bulk_commit();
            const bool gjob = i == 0 && outjob;
            if (!gjob) { bulk_wait_read(); mbar_arrive(ste); }
            bulk_wait_all();
            if (ty == IT_FFN) flag_add_relaxed(v < 5 ? FL_H1 + u : FL_H2 + u, 1);
            if (ty == IT_HALF) flag_add_relaxed(FL_H2 + u + w, 2);
          }
          __syncwarp();
          if (i == 0 && b >= 88 && b < 128 && lane < 16) flag_add_relaxed(FL_AW + lane, 1);
          if (i == 0 && outjob) {
            const uint32_t gb = bar_gate + 8 * w;
            const int row0 = 16 * b + 8 * w;
            if (lane == 0) {
              mbar_expect_tx(gb, 10240 + 1280);
              bulk_ld(stg, P.xp + row0 * D_, 10240, gb);
              bulk_ld(stg + 10240, P.gw, 1280, gb);
            }
            __syncwarp();
            mbar_wait(gb, 0);
            float c0 = 0.f, c1 = 0.f;
            const int row = lane >> 2;
            const uint32_t c16 = ((lane & 3) ^ ((row & 1) << 2)) * 16;
#pragma unroll 4
            for (int q = 0; q < 20; q++) {
              const uint32_t off = (q * 64) ^ (c16 & 64), o2 = off + (c16 & 63);
              uint4 xv = lds128(stg + row * 1280 + o2);
              const uint4 wv = lds128(stg + 10240 + o2);
              asm("mul.rn.bf16x2 %0, %0, %1;" : "+r"(xv.x) : "r"(wv.x));
              asm("mul.rn.bf16x2 %0, %0, %1;" : "+r"(xv.y) : "r"(wv.y));
              asm("mul.rn.bf16x2 %0, %0, %1;" : "+r"(xv.z) : "r"(wv.z));
              asm("mul.rn.bf16x2 %0, %0, %1;" : "+r"(xv.w) : "r"(wv.w));
              c0 += (bf_lo(xv.x) + bf_hi(xv.x)) + (bf_lo(xv.y) + bf_hi(xv.y));
              c1 += (bf_lo(xv.z) + bf_hi(xv.z)) + (bf_lo(xv.w) + bf_hi(xv.w));
            }
            c0 += c1;
            c0 += __shfl_xor_sync(0xffffffffu, c0, 1);
            c0 += __shfl_xor_sync(0xffffffffu, c0, 2);
            if ((lane & 3) == 0) {
              const float logit = __bfloat162float(__float2bfloat16_rn(c0));
              const float gg = __bfloat162float(__float2bfloat16_rn(__fdividef(1.0f, 1.0f + __expf(-logit))));
              g_gate[row0 + row] = make_float2(gg, __bfloat162float(__float2bfloat16_rn(1.0f - gg)));
            }
            __syncwarp();
            if (lane == 0) {
              mbar_arrive(ste);
              flag_add(FL_G + (b >> 3), 1);
            }
          }
          __syncwarp();
        }
        for (int j = w; j < nch; j += 2) {
          const int ch = chain_id(b, j);
          if (lane == 0) {
            mbar_wait(stf, ph); ph ^= 1;
            if (ch == 0) {
              tma_st2d(&P.zst32, stg, 0, 0);
              tma_st2d(&P.zst32, stg + 8192, 0, 10240);
            } else if (ch == 1) {
              tma_st2d(&P.zst32, stg, 0, 32);
              tma_st2d(&P.zst32, stg + 8192 + 4096, 0, 10240 + 32);
            } else {
              tma_st2d(&P.zst64, stg, 0, (ch - 1) * 64);
              tma_st2d(&P.zst64, stg + 8192, 0, 10240 + (ch - 1) * 64);
            }
            bulk_commit();
            bulk_wait_read();
            mbar_arrive(ste);
            bulk_wait_all();
          }
          __syncwarp();
          flag_add_relaxed(FL_Z + (ch < 2 ? 0 : (ch - 1) >> 5) * 32 + lane, 1);
        }
        if (lane == 0) {
          if (outjob && mate_is_partner(bar_mate, matew, b)) mbar_arrive_cluster(mapa(bar_rdy + 8 * w, crank ^ 1));
        }
      } else {
        if (lane == 0) {
          asm volatile("st.async.weak.shared::cluster.mbarrier::complete_tx::bytes.b32 [%0], %1, [%2];"
                       :: "r"(mapa(matew, crank ^ 1)), "r"(b), "r"(mapa(bar_mate, crank ^ 1)) : "memory");
          mbar_wait_cluster(bar_mate, 0);
        }
        if (lane == 0 && b < 4) l2_prefetch((const uint8_t*)P.Cp + b * 10240, 10240);
        int m, n_;
        out_tile(b, m, n_);
        if (outjob) {
          if (lane == 0) {
            wait_kb(kbw, WDPF_KB);
            l2_prefetch(P.wdp + b * 8640, 17280);
            l2_prefetch(P.TEp + b * 1600, 3200);
          }
          mbar_wait(bar_go, 0);
        }
        int fl = FL_AW + ((b >> 3) & 15); unsigned tg = 208;
        if (lane == 0 && b >= 124) { fl = FL_A0; tg = 128 + 16; }
        if (lane == 1) { fl = FL_G + m; tg = 16; }
        if (lane == 2) { fl = FL_H1 + m; tg = 10; }
        if (lane == 3) { fl = FL_H2 + m; tg = 18; }
        if (lane >= 4 && lane < 9) { fl = FL_Z + (lane - 4) * 32 + ((b >> 2) & 31); tg = lane == 4 ? 33 : 32; }
        const int last = !outjob ? 2 : 8;
        const unsigned skip = (nch == 0 ? 1 : 0) | (b < 124 ? 0x200 : 0) | (outjob ? 0 : 4);
        int level = 0;
        bool gates = false;
        const unsigned* fp = &g_flags[fl * 32];
        unsigned seen = skip;
        auto step = [&](unsigned& va, unsigned& vb) {
          const bool want = (lane < (level >= 3 ? 9 : 4) || lane == 9) && !((seen >> lane) & 1) && (outjob || lane == 0 || lane == 9);
          asm volatile("{\n.reg .pred p;\nsetp.ne.u32 p, %2, 0;\nmov.u32 %0, 0;\n@p ld.relaxed.gpu.global.u32 %0, [%1];\n}" : "=r"(va) : "l"(fp), "r"((unsigned)want) : "memory");
          seen |= __ballot_sync(0xffffffffu, vb >= tg);
          if (outjob && !gates && (seen & 2)) {
            gates = true;
            const float4* gp = (const float4*)(g_gate + m * 128);
            const float4 q0 = __ldcg(gp + lane), q1 = __ldcg(gp + 32 + lane);
            asm volatile("st.shared.v4.f32 [%0], {%1, %2, %3, %4};" :: "r"(sb + OFF_G + lane * 16), "f"(q0.x), "f"(q0.y), "f"(q0.z), "f"(q0.w) : "memory");
            asm volatile("st.shared.v4.f32 [%0], {%1, %2, %3, %4};" :: "r"(sb + OFF_G + 512 + lane * 16), "f"(q1.x), "f"(q1.y), "f"(q1.z), "f"(q1.w) : "memory");
            __threadfence_block();
            __syncwarp();
          }
          int nl = 0;
          if (seen & 1) {
            nl = 1;
            if ((seen & 0x204) == 0x204) {
              nl = 2;
              if (gates && (seen & 8)) nl = 3 + (__ffs(~((seen >> 4) & 31)) - 1);
            }
          }
          if (nl > last) nl = last;
          if (nl > level) {
            if (lane == 0) {
              asm volatile("st.volatile.shared.u32 [%0], %1;" :: "r"(prog), "r"(nl) : "memory");
            }
            level = nl;
          }
        };
        unsigned va = 0;
        for (int it = 0; it < LIM_FLAG && level < last; it++) {
          step(va, va);
        }
        __syncwarp();
        int last_cta = 0;
        if (lane == 0) {
          unsigned old;
          asm volatile("atom.acq_rel.gpu.global.inc.u32 %0, [%1], %2;" : "=r"(old) : "l"(&g_flags[FL_DONE * 32]), "r"(NCTA - 1) : "memory");
          last_cta = old == NCTA - 1;
        }
        if (__shfl_sync(0xffffffffu, last_cta, 0))
          for (int f = lane; f < FL_DONE; f += 32) g_flags[f * 32] = 0;
      }
      __syncwarp();
    }
    if (warp == 8) asm volatile("barrier.cluster.wait.aligned;" ::: "memory");
  } else {
    reg_inc<224>();
    const int w = warp >> 2;
    const int ww = warp & 3;
    const int t128 = tid & 127;
    const uint32_t stg = sb + OFF_STG + w * 16384, stf = bar_stf + 8 * w, ste = bar_ste + 8 * w;
    uint32_t ste_ph = 1;
    if (w == 1) turn_pass(1);
    Ring rg{0xE4, 0, 0};
    const int sm_row = ww * 16 + ((lane >> 3) & 1) * 8 + (lane & 7);
    const int sm_cg = lane >> 4;

    const uint32_t sb4 = a16(sb);
    constexpr uint64_t DK = desc_hi(16, 1024);
    constexpr uint64_t DN = desc_hi(8192, 1024);

    {
      float acc[128];
      zero_regs(acc);
      for (int i = 0; i < ng1; i++) {
        int u, v;
        const int ty = get_item(b, i, u, v);
        const int ls = i == 0 ? 1 : (b >= 88 ? LAG_DFT : LAG);
        const bool fin = !outjob && w == 1;
        uint32_t prev = 0;
        bool pend = false;
        if (ty == IT_HALF) break;
        if (ty == IT_FFN) {
          for (int kb = 0; kb < 10; kb++) {
            const uint32_t sl = rg.slot(), a4 = sb4 + sl * (STAGE_BYTES / 16), aw4 = a4 + w * 512;
            mbar_wait(bar_full + 8 * sl, rg.par(sl));
            if (tid == 0 && i == 0) asm volatile("st.volatile.shared.u32 [%0], %1;" :: "r"(kbw), "r"(kb + 1) : "memory");
            if (seg_wait(kb, 10, ls, LAG)) turn_wait(w);
            wg_fence();
#pragma unroll
            for (int kk = 0; kk < 4; kk++)
              wgmma_n256_ss<0, 1>(acc, dsc(aw4, kk * 32, DK), dsc(a4, 16384 + kk * 2048, DN), kb | kk);
            wg_commit();
            if (seg_pass(kb, 10, ls, LAG) && !(fin && kb == 9)) turn_pass(w);
            RELEASE_SLOT(kb >= (i == 0 ? ER_FROM0 : ER_FROM1) && kb < 9 && seg_wait(kb + 1, 10, ls, LAG));
            prev = sl; rg.next(sl);
          }
          wg_wait<0>();
          fence_regs(acc);
          RELEASE_LAST();
          if (i == 0 && outjob) mbar_wait(bar_go, 0);
          mbar_wait(ste, ste_ph); ste_ph ^= 1;
#pragma unroll
          for (int j = 0; j < 16; j += 2) {
            uint32_t r[4];
#pragma unroll
            for (int q = 0; q < 2; q++) {
              const int jj = j + q;
              r[2 * q + 0] = reglu2(acc[4 * jj], acc[4 * jj + 1], acc[64 + 4 * jj], acc[64 + 4 * jj + 1]);
              r[2 * q + 1] = reglu2(acc[4 * jj + 2], acc[4 * jj + 3], acc[64 + 4 * jj + 2], acc[64 + 4 * jj + 3]);
            }
            stsm4(stg + (j >> 3) * 8192 + sm_row * 128 + ((((j & 7) + sm_cg) ^ (sm_row & 7)) << 4), r[0], r[1], r[2], r[3]);
          }
          fence_async_smem();
          STF_ARRIVE(stf);
        } else {
          for (int kb = 0; kb < 10; kb++) {
            const uint32_t sl = rg.slot(), a4 = sb4 + sl * (STAGE_BYTES / 16), aw4 = a4 + w * 512;
            mbar_wait(bar_full + 8 * sl, rg.par(sl));
            if (tid == 0) asm volatile("st.volatile.shared.u32 [%0], %1;" :: "r"(kbw), "r"(kb + 1) : "memory");
            if (seg_wait(kb, 10, ls, LAG)) turn_wait(w);
            wg_fence();
#pragma unroll
            for (int kk = 0; kk < 4; kk++)
              wgmma_n256_ss<0, 0>(acc, dsc(aw4, kk * 32, DK), dsc(a4, 16384 + kk * 32, DK), kb | kk);
            wg_commit();
            if (seg_pass(kb, 10, ls, LAG)) turn_pass(w);
            RELEASE_SLOT(kb >= (i == 0 ? ER_FROM0 : ER_FROM1) && kb < 9 && seg_wait(kb + 1, 10, ls, LAG));
            prev = sl; rg.next(sl);
          }
          wg_wait<0>();
          fence_regs(acc);
          RELEASE_LAST();
          mbar_wait(bar_go, 0);
#pragma unroll
          for (int hf = 0; hf < 2; hf++) {
            const uint32_t sg = sb + OFF_STG + hf * 16384;
            mbar_wait(bar_ste + 8 * hf, w ^ 1);
#pragma unroll
            for (int j = 0; j < 16; j += 2) {
              const int jj = hf * 16 + j;
              stsm4(sg + (j >> 3) * 8192 + sm_row * 128 + ((((j & 7) + sm_cg) ^ (sm_row & 7)) << 4),
                    pack2(acc[4 * jj], acc[4 * jj + 1]), pack2(acc[4 * jj + 2], acc[4 * jj + 3]),
                    pack2(acc[4 * jj + 4], acc[4 * jj + 5]), pack2(acc[4 * jj + 6], acc[4 * jj + 7]));
            }
            fence_async_smem();
            STF_ARRIVE(bar_stf + 8 * hf);
          }
        }
      }
    }

    {
      int u, v;
      if (ng1 == 2 && get_item(b, 1, u, v) == IT_HALF) {
        float h0[64], h1[64];
        undef_regs(h0);
        undef_regs(h1);
        uint32_t prev = 0;
        bool pend = false;
        for (int kb = 0; kb < 10; kb++) {
          const uint32_t sl = rg.slot(), a4 = sb4 + sl * (STAGE_BYTES / 16), aw4 = a4 + w * 1024;
          mbar_wait(bar_full + 8 * sl, rg.par(sl));
          if (seg_wait(kb, 10, LAG, LAG)) turn_wait(w);
          wg_fence();
#pragma unroll
          for (int kk = 0; kk < 4; kk++) {
            wgmma_n128_ss<0, 1>(h0, dsc(aw4, kk * 32, DK), dsc(a4, 32768 + kk * 2048, DN), kb | kk);
            wgmma_n128_ss<0, 1>(h1, dsc(aw4, 8192 + kk * 32, DK), dsc(a4, 32768 + kk * 2048, DN), kb | kk);
          }
          wg_commit();
          if (seg_pass(kb, 10, LAG, LAG)) turn_pass(w);
          RELEASE_SLOT(kb >= ER_FROM1 && kb < 9 && seg_wait(kb + 1, 10, LAG, LAG));
          prev = sl; rg.next(sl);
        }
        wg_wait<0>();
        fence_regs(h0);
        fence_regs(h1);
        RELEASE_LAST();
        mbar_wait(ste, ste_ph); ste_ph ^= 1;
#pragma unroll
        for (int j = 0; j < 8; j += 2) {
          uint32_t r[4], r2[4];
#pragma unroll
          for (int q = 0; q < 2; q++) {
            const int o = 4 * (j + q);
            r[2 * q + 0] = reglu2(h0[o], h0[o + 1], h0[o + 32], h0[o + 33]);
            r[2 * q + 1] = reglu2(h0[o + 2], h0[o + 3], h0[o + 34], h0[o + 35]);
            r2[2 * q + 0] = reglu2(h1[o], h1[o + 1], h1[o + 32], h1[o + 33]);
            r2[2 * q + 1] = reglu2(h1[o + 2], h1[o + 3], h1[o + 34], h1[o + 35]);
          }
          const uint32_t ad = stg + sm_row * 128 + (((j + sm_cg) ^ (sm_row & 7)) << 4);
          stsm4(ad, r[0], r[1], r[2], r[3]);
          stsm4(ad + 8192, r2[0], r2[1], r2[2], r2[3]);
        }
        fence_async_smem();
        STF_ARRIVE(stf);
      }
    }

    if (nch > 0) {
      const uint32_t cslot = ng1 == 2 ? 0 : 2;
      rg.phm = ng1 == 2 ? 0xF : 0x3;
      const uint32_t sC = sb + cslot * STAGE_BYTES, c4 = sb4 + cslot * (STAGE_BYTES / 16);
      mbar_wait(bar_full + 8 * cslot, rg.par(cslot));
      for (int j = w; j < nch; j += 2) {
        const uint32_t slot = rg.islot(cslot, j);
        const bool packed = nch == 2;
        const uint32_t slot0 = packed ? rg.islot(cslot, 0) : slot;
        const uint32_t sA = sb + slot0 * STAGE_BYTES + (packed ? w * 16384 : 0);
        const uint32_t sW = packed ? (w == 0 ? sA + 32768 : sb + slot * STAGE_BYTES) : sA + 16384;
        mbar_wait(bar_full + 8 * slot0, rg.ipar(cslot, packed ? 0 : j));
        const bool special = b == 1 && j == 0;
        const uint32_t twa = sC + 32768;
        float acc1[64];
        float zr[32], zi[32];
        zero_regs(acc1);
        zero_regs(zr);
        zero_regs(zi);
        wg_fence();
        {
          const uint64_t dz = desc_hi(8192, 1024) + (special ? ((uint64_t)(4096 >> 4) << 16) : 0);
          const uint32_t x4 = sb4 + ((sA - sb) >> 4), k2 = special ? 0 : 4;
          wgmma_n128_ss<0, 1>(acc1, dsc(c4, 16384, DK), dsc(x4, 0, dz), 0);
          wgmma_n128_ss<0, 1>(acc1, dsc(c4, 16384 + 32, DK), dsc(x4, 2048, dz), 1);
          wgmma_n128_ss<0, 1>(acc1, dsc(c4 + k2, 16384, DK), dsc(x4 + 64 * k2, 0, dz), 1);
          wgmma_n128_ss<0, 1>(acc1, dsc(c4 + k2, 16384 + 32, DK), dsc(x4 + 64 * k2, 2048, dz), 1);
        }
        wg_commit();
        uint32_t twr[8], twi[8], twn[8];
#pragma unroll
        for (int q = 0; q < 4; q++) { const uint4 v4 = lds128(twa + q * 2048 + t128 * 16); twr[2 * q] = v4.x; twi[2 * q] = v4.y; twr[2 * q + 1] = v4.z; twi[2 * q + 1] = v4.w; }
#pragma unroll
        for (int q = 0; q < 8; q++) twn[q] = hneg2(twi[q]);
        wg_wait<0>();
        fence_regs(acc1);
        uint32_t are[16], aim[16];
#pragma unroll
        for (int c = 0; c < 2; c++)
#pragma unroll
          for (int q = 0; q < 8; q++) {
            const uint32_t tr = pack2(acc1[32 * c + 4 * q], acc1[32 * c + 4 * q + 1]), ti = pack2(acc1[32 * c + 4 * q + 2], acc1[32 * c + 4 * q + 3]);
            are[(q >> 1) * 4 + (q & 1) * 2 + c] = hfma2(ti, twn[q], hmul2(tr, twr[q]));
            aim[(q >> 1) * 4 + (q & 1) * 2 + c] = hfma2(ti, twr[q], hmul2(tr, twi[q]));
          }
        wg_fence();
#pragma unroll
        for (int kk = 0; kk < 4; kk++) {
          wgmma_n64_rs<1, 1>(zr, are[4 * kk], are[4 * kk + 1], are[4 * kk + 2], are[4 * kk + 3], dsc(c4, kk * 2048, DN), kk != 0);
          wgmma_n64_rs<1, 1>(zi, are[4 * kk], are[4 * kk + 1], are[4 * kk + 2], are[4 * kk + 3], dsc(c4, 8192 + kk * 2048, DN), kk != 0);
        }
#pragma unroll
        for (int kk = 0; kk < 4; kk++) {
          wgmma_n64_rs<1, -1>(zr, aim[4 * kk], aim[4 * kk + 1], aim[4 * kk + 2], aim[4 * kk + 3], dsc(c4, 8192 + kk * 2048, DN), 1);
          wgmma_n64_rs<1, 1>(zi, aim[4 * kk], aim[4 * kk + 1], aim[4 * kk + 2], aim[4 * kk + 3], dsc(c4, kk * 2048, DN), 1);
        }
        wg_commit();
        uint4 wv[8];
        if (packed && w == 1) mbar_wait(bar_full + 8 * slot, rg.ipar(cslot, j));
#pragma unroll
        for (int q = 0; q < 8; q++) wv[q] = lds128(sW + q * 2048 + t128 * 16);
        named_sync(1 + w, 128);
        if (t128 == 0) {
          mbar_arrive(bar_empty + 8 * slot0);
          if (!packed || w == 1) mbar_arrive(bar_empty + 8 * slot);
          if (packed && w == 1) mbar_arrive(bar_empty + 8 * slot);
        }
        wg_wait<0>();
        fence_regs(zr);
        fence_regs(zi);
#pragma unroll
        for (int c = 0; c < 2; c++)
#pragma unroll
          for (int q = 0; q < 8; q++) {
            const uint32_t a0 = pack2(zr[4 * q + 2 * c], zr[4 * q + 2 * c + 1]), b0 = pack2(zi[4 * q + 2 * c], zi[4 * q + 2 * c + 1]);
            const uint4 q4 = wv[4 * c + (q >> 1)];
            const uint32_t wr = (q & 1) ? q4.z : q4.x, wi = (q & 1) ? q4.w : q4.y;
            are[(q >> 1) * 4 + (q & 1) * 2 + c] = hfma2(b0, hneg2(wi), hmul2(a0, wr));
            aim[(q >> 1) * 4 + (q & 1) * 2 + c] = hfma2(a0, wi, hmul2(b0, wr));
          }
        wg_fence();
#pragma unroll
        for (int kk = 0; kk < 4; kk++) {
          wgmma_n64_rs<1, 1>(zr, are[4 * kk], are[4 * kk + 1], are[4 * kk + 2], are[4 * kk + 3], dsc(c4, kk * 2048, DN), kk != 0);
          wgmma_n64_rs<1, -1>(zi, are[4 * kk], are[4 * kk + 1], are[4 * kk + 2], are[4 * kk + 3], dsc(c4, 8192 + kk * 2048, DN), kk != 0);
        }
#pragma unroll
        for (int kk = 0; kk < 4; kk++) {
          wgmma_n64_rs<1, 1>(zr, aim[4 * kk], aim[4 * kk + 1], aim[4 * kk + 2], aim[4 * kk + 3], dsc(c4, 8192 + kk * 2048, DN), 1);
          wgmma_n64_rs<1, 1>(zi, aim[4 * kk], aim[4 * kk + 1], aim[4 * kk + 2], aim[4 * kk + 3], dsc(c4, kk * 2048, DN), 1);
        }
        wg_commit();
        mbar_wait(ste, ste_ph); ste_ph ^= 1;
        wg_wait<0>();
        fence_regs(zr);
        fence_regs(zi);
#pragma unroll
        for (int c = 0; c < 2; c++)
#pragma unroll
          for (int q = 0; q < 8; q += 2) {
            uint32_t rr[4];
#pragma unroll
            for (int h = 0; h < 2; h++) {
              const int jj = q + h;
              const uint32_t ur = pack2(zr[4 * jj + 2 * c], zr[4 * jj + 2 * c + 1]), ui = pack2(zi[4 * jj + 2 * c], zi[4 * jj + 2 * c + 1]);
              rr[2 * h] = hfma2(ui, twi[jj], hmul2(ur, twr[jj]));
              rr[2 * h + 1] = hfma2(ur, twn[jj], hmul2(ui, twr[jj]));
            }
            stsm4(stg + c * 8192 + sm_row * 128 + (((q + sm_cg) ^ (sm_row & 7)) << 4), rr[0], rr[1], rr[2], rr[3]);
          }
        fence_async_smem();
        named_sync(1 + w, 128);
        wg_fence();
#pragma unroll
        for (int kk = 0; kk < 4; kk++)
          wgmma_n128_ss<0, 1>(acc1, dsc(c4, 24576 + kk * 32, DK), dsc(sb4 + OFF_STG / 16 + w * 1024, kk * 2048, DN), kk != 0);
        wg_commit();
        wg_wait<0>();
        fence_regs(acc1);
        named_sync(1 + w, 128);
        {
          const int orow = ((lane >> 3) & 1) * 32 + 8 * ww + (lane & 7);
#pragma unroll
          for (int q = 0; q < 8; q += 2) {
            const uint32_t ad = stg + orow * 128 + (((q + sm_cg) ^ (lane & 7)) << 4);
            const float* A = acc1 + 4 * q;
            const float* B = acc1 + 32 + 4 * q;
            stsm4(ad, pack2(A[0] + B[0], A[1] + B[1]), pack2(A[2] - B[2], A[3] - B[3]), pack2(A[4] + B[4], A[5] + B[5]), pack2(A[6] - B[6], A[7] - B[7]));
            stsm4(ad + 8192, pack2(A[0] - B[0], A[1] - B[1]), pack2(A[2] + B[2], A[3] + B[3]), pack2(A[4] - B[4], A[5] - B[5]), pack2(A[6] + B[6], A[7] + B[7]));
          }
        }
        fence_async_smem();
        STF_ARRIVE(stf);
      }
      if (t128 == 0) mbar_arrive(bar_empty + 8 * cslot);
    }
    rg.ord = nch == 0 ? 0xE4 : nch == 2 ? 0x27 : 0xB4;
    rg.phm = nch == 0 ? 0xF : nch == 2 ? 0x8 : 0x4;
    rg.i = 0;

    if (outjob) {
      const int rank = b & 1;
      int m, n;
      out_tile(b, m, n);
      const int np = n_ffn_p(b);
      float acc[80];
      uint32_t prev = 0;
      bool pend = false;
      const uint32_t gaddr = sb + OFF_G + (w * 64 + ww * 16 + (lane >> 2)) * 8;
      bool direct = true;
      uint32_t rdst = 0;
      float keep[40];
      uint32_t goff[5];
      auto out_addr = [&]() {
#pragma unroll
        for (int q = 0; q < 5; q++) {
          const int c = q * 128 + t128, r = c / 10, k = c - 10 * r;
          const int col = ((n & 1) && rank) ? (k < 6 ? 112 + 8 * k : 8 * k - 48) : ((n & 1) ? 32 : rank * 80) + 8 * k;
          goff[q] = ((m * 128 + w * 64 + r) * D_ + n * 160 + col) * 2;
          asm volatile("" : "+r"(goff[q]) :: "memory");
        }
      };
      {
        float es[40];
        float g0, o0, g1, o1;
        const int nf = rank ? 27 - np : np, nt = nf + 5;
        const int lags = nch > 0 ? LAGS_Q : LAGS;
        undef_regs(acc);
        undef_regs(es);
        for (int kb = 0; kb < nf; kb++) {
          const uint32_t sl = rg.slot(), a4 = sb4 + sl * (STAGE_BYTES / 16), aw4 = a4 + w * 512;
          mbar_wait(bar_full + 8 * sl, rg.par(sl));
          if (seg_wait(kb, nt, lags, LAGE)) turn_wait(w);
          wg_fence();
#pragma unroll
          for (int kk = 0; kk < 4; kk++)
            wgmma_n160_ss<0, 1>(acc, dsc(aw4, kk * 32, DK), dsc(a4, 16384 + kk * 2048, DN), kb | kk);
          wg_commit();
          if (seg_pass(kb, nt, lags, LAGE)) turn_pass(w);
          RELEASE_SLOT(kb >= ER_FROMD && seg_wait(kb + 1, nt, lags, LAGE));
          prev = sl; rg.next(sl);
        }
        uint32_t es4[3];
#pragma unroll
        for (int k = 0; k < 3; k++) { const uint32_t sl = rg.slot(); es4[k] = sb4 + sl * (STAGE_BYTES / 16); rg.next(sl); }
#pragma unroll
        for (int i = 0; i < 5; i++) {
          const uint32_t ay4 = e_addr_y(es4, i, 4) + w * 512, at4 = e_addr_t(es4, i, 4);
          mbar_wait(bar_ef + 8 * i, 0);
          if (seg_wait(nf + i, nt, lags, LAGE)) turn_wait(w);
          wg_fence();
#pragma unroll
          for (int kk = 0; kk < 4; kk++)
            wgmma_n80_ss<1, 0>(es, dsc(ay4, kk * 2048, DN), dsc(at4, kk * 32, DK), i | kk);
          wg_commit();
          if (seg_pass(nf + i, nt, lags, LAGE) && !(w == 1 && i == 4)) turn_pass(w);
          if (i == XEARLY) {
            g0 = lds32f(gaddr); o0 = lds32f(gaddr + 4); g1 = lds32f(gaddr + 64); o1 = lds32f(gaddr + 68);
            direct = mate_is_partner(bar_mate, matew, b);
            rdst = mapa(stg + t128 * 16, crank ^ 1);
            wg_wait<1>();
            fence_regs(acc);
#pragma unroll
            for (int q = 0; q < 80; q++) acc[q] *= ((q >> 1) & 1) ? o1 : o0;
            asm volatile("barrier.cluster.wait.aligned;" ::: "memory");
            if (direct) {
              mbar_wait_cluster(bar_rdy + 8 * w, 0);
              const uint32_t rbar = mapa(bar_rx + 8 * w, crank ^ 1);
              if (rank == 0) {
#pragma unroll
                for (int q = 0; q < 5; q++)
                  asm volatile("st.async.weak.shared::cluster.mbarrier::complete_tx::bytes.v4.b32 [%0], {%1, %2, %3, %4}, [%5];"
                    :: "r"(rdst + q * 2048), "r"(pack2(acc[40 + 8 * q], acc[41 + 8 * q])), "r"(pack2(acc[42 + 8 * q], acc[43 + 8 * q])),
                       "r"(pack2(acc[44 + 8 * q], acc[45 + 8 * q])), "r"(pack2(acc[46 + 8 * q], acc[47 + 8 * q])), "r"(rbar) : "memory");
              } else {
#pragma unroll
                for (int q = 0; q < 5; q++)
                  asm volatile("st.async.weak.shared::cluster.mbarrier::complete_tx::bytes.v4.b32 [%0], {%1, %2, %3, %4}, [%5];"
                    :: "r"(rdst + q * 2048), "r"(pack2(acc[8 * q], acc[1 + 8 * q])), "r"(pack2(acc[2 + 8 * q], acc[3 + 8 * q])),
                       "r"(pack2(acc[4 + 8 * q], acc[5 + 8 * q])), "r"(pack2(acc[6 + 8 * q], acc[7 + 8 * q])), "r"(rbar) : "memory");
              }
            }
          }
        }
        wg_wait<0>();
        fence_regs(es);
        if (direct) {
          const uint32_t rbar2 = mapa(bar_rx2 + 8 * w, crank ^ 1);
          uint32_t lw[10];
          if (rank == 0) {
#pragma unroll
            for (int q = 0; q < 10; q++) { const float g = (q & 1) ? g1 : g0; lw[q] = pack2(es[20 + 2 * q] * g, es[21 + 2 * q] * g); }
          } else {
#pragma unroll
            for (int q = 0; q < 10; q++) { const float g = (q & 1) ? g1 : g0; lw[q] = pack2(es[2 * q] * g, es[1 + 2 * q] * g); }
          }
          asm volatile("st.async.weak.shared::cluster.mbarrier::complete_tx::bytes.v4.b32 [%0], {%1, %2, %3, %4}, [%5];"
            :: "r"(rdst + 10240), "r"(lw[0]), "r"(lw[1]), "r"(lw[2]), "r"(lw[3]), "r"(rbar2) : "memory");
          asm volatile("st.async.weak.shared::cluster.mbarrier::complete_tx::bytes.v4.b32 [%0], {%1, %2, %3, %4}, [%5];"
            :: "r"(rdst + 12288), "r"(lw[4]), "r"(lw[5]), "r"(lw[6]), "r"(lw[7]), "r"(rbar2) : "memory");
          asm volatile("st.async.weak.shared::cluster.mbarrier::complete_tx::bytes.v2.b32 [%0], {%1, %2}, [%3];"
            :: "r"(rdst + 14336 - t128 * 8), "r"(lw[8]), "r"(lw[9]), "r"(rbar2) : "memory");
          out_addr();
          mbar_wait_cluster(bar_rx + 8 * w, 0);
          uint32_t rw[20];
#pragma unroll
          for (int q = 0; q < 5; q++) {
            const uint4 v = lds128(stg + q * 2048 + t128 * 16);
            rw[4 * q] = v.x; rw[4 * q + 1] = v.y; rw[4 * q + 2] = v.z; rw[4 * q + 3] = v.w;
          }
          if (rank == 0) {
#pragma unroll
            for (int e = 0; e < 20; e++) { keep[2 * e] = acc[2 * e] + bf_lo(rw[e]); keep[2 * e + 1] = acc[2 * e + 1] + bf_hi(rw[e]); }
          } else {
#pragma unroll
            for (int e = 0; e < 20; e++) { keep[2 * e] = acc[40 + 2 * e] + bf_lo(rw[e]); keep[2 * e + 1] = acc[41 + 2 * e] + bf_hi(rw[e]); }
          }
          if (rank == 0) {
#pragma unroll
            for (int q = 0; q < 40; q += 4)
#pragma unroll
              for (int h = 0; h < 2; h++) keep[q + 2 * h] = fmaf(es[4 * (q >> 3) + 2 * h + ((q >> 2) & 1)], h ? g1 : g0, keep[q + 2 * h]);
          } else {
#pragma unroll
            for (int q = 0; q < 40; q += 4)
#pragma unroll
              for (int h = 0; h < 2; h++) keep[q + 2 * h + 1] = fmaf(es[20 + 4 * (q >> 3) + 2 * h + ((q >> 2) & 1)], h ? g1 : g0, keep[q + 2 * h + 1]);
          }
          mbar_wait_cluster(bar_rx2 + 8 * w, 0);
          const uint4 l0 = lds128(stg + 10240 + t128 * 16), l1 = lds128(stg + 12288 + t128 * 16);
          uint32_t l8, l9;
          asm volatile("ld.shared.v2.u32 {%0, %1}, [%2];" : "=r"(l8), "=r"(l9) : "r"(stg + 14336 + t128 * 8) : "memory");
          const uint32_t lr[10] = {l0.x, l0.y, l0.z, l0.w, l1.x, l1.y, l1.z, l1.w, l8, l9};
          if (rank == 0) {
#pragma unroll
            for (int q = 0; q < 40; q += 2) {
              const int j = q >> 2, h = (q >> 1) & 1;
              const uint32_t wd = lr[2 * (j >> 1) + h];
              keep[q + 1] += (j & 1) ? bf_hi(wd) : bf_lo(wd);
            }
          } else {
#pragma unroll
            for (int q = 0; q < 40; q += 2) {
              const int j = q >> 2, h = (q >> 1) & 1;
              const uint32_t wd = lr[2 * (j >> 1) + h];
              keep[q] += (j & 1) ? bf_hi(wd) : bf_lo(wd);
            }
          }
        } else {
#pragma unroll
          for (int q = 0; q < 80; q += 2) {
            const int j = q >> 2, h = (q >> 1) & 1;
            const float sp = es[4 * (j >> 1) + 2 * h + (j & 1)] * (h ? g1 : g0);
            acc[q] += rank ? 0.f : sp;
            acc[q + 1] += rank ? sp : 0.f;
          }
          uint4* xch = (uint4*)g_X1T;
          uint4* mine = xch + (b * 2 + w) * 640 + t128;
          const uint4* theirs = xch + ((b ^ 1) * 2 + w) * 640 + t128;
#pragma unroll
          for (int q = 0; q < 5; q++) {
            const int o = rank == 0 ? 1 : 0;
            uint32_t r4[4];
#pragma unroll
            for (int e = 0; e < 4; e++)
              r4[e] = o ? pack2(acc[40 + 8 * q + 2 * e], acc[41 + 8 * q + 2 * e]) : pack2(acc[8 * q + 2 * e], acc[1 + 8 * q + 2 * e]);
            __stcg(mine + q * 128, make_uint4(r4[0], r4[1], r4[2], r4[3]));
          }
#pragma unroll
          for (int q = 0; q < 40; q++) keep[q] = rank == 0 ? acc[q] : acc[40 + q];
          __threadfence();
          named_sync(1 + w, 128);
          unsigned* fx = &g_flags[FL_X * 32];
          if (t128 == 0) {
            atomicAdd(fx + b * 2 + w, 1);
            int it = 0;
            while (atomicExch(fx + (b ^ 1) * 2 + w, 0) == 0 && ++it < LIM_FLAG) __nanosleep(100);
            if (it >= LIM_FLAG) TIMEOUT(0x40000);
            __threadfence();
          }
          named_sync(1 + w, 128);
#pragma unroll
          for (int q = 0; q < 5; q++) {
            const uint4 v = __ldcg(theirs + q * 128);
            const uint32_t r4[4] = {v.x, v.y, v.z, v.w};
#pragma unroll
            for (int e = 0; e < 4; e++) { keep[8 * q + 2 * e] += bf_lo(r4[e]); keep[8 * q + 2 * e + 1] += bf_hi(r4[e]); }
          }
          mbar_wait(ste, ste_ph);
          out_addr();
        }
      }
      named_sync(1 + w, 128);
#pragma unroll
      for (int q = 0; q < 5; q++)
        stsm4(stg + sm_row * 160 + (2 * q + sm_cg) * 16, pack2(keep[8 * q], keep[8 * q + 1]), pack2(keep[8 * q + 2], keep[8 * q + 3]),
              pack2(keep[8 * q + 4], keep[8 * q + 5]), pack2(keep[8 * q + 6], keep[8 * q + 7]));
      named_sync(1 + w, 128);
#pragma unroll
      for (int q = 0; q < 5; q++) {
        const uint4 v = lds128(stg + (q * 128 + t128) * 16);
        asm volatile("st.global.v4.b32 [%0], {%1, %2, %3, %4};" :: "l"((uint8_t*)P.outp + goff[q]), "r"(v.x), "r"(v.y), "r"(v.z), "r"(v.w) : "memory");
      }
    }
    else asm volatile("barrier.cluster.wait.aligned;" ::: "memory");
  }
}

typedef CUresult (*EncodeFn)(CUtensorMap*, CUtensorMapDataType, cuuint32_t, void*, const cuuint64_t*, const cuuint64_t*, const cuuint32_t*, const cuuint32_t*,
                             CUtensorMapInterleave, CUtensorMapSwizzle, CUtensorMapL2promotion, CUtensorMapFloatOOBfill);

void enc(EncodeFn fn, CUtensorMap* m, const void* base, int rank, const cuuint64_t* dims, const cuuint64_t* strides, const cuuint32_t* box, bool swz) {
  cuuint32_t es[3] = {1, 1, 1};
  fn(m, CU_TENSOR_MAP_DATA_TYPE_BFLOAT16, rank, const_cast<void*>(base), dims, strides, box, es, CU_TENSOR_MAP_INTERLEAVE_NONE,
     swz ? CU_TENSOR_MAP_SWIZZLE_128B : CU_TENSOR_MAP_SWIZZLE_NONE, CU_TENSOR_MAP_L2_PROMOTION_L2_128B, CU_TENSOR_MAP_FLOAT_OOB_FILL_NONE);
}
void enc2(EncodeFn fn, CUtensorMap* m, const void* base, uint64_t inner, uint64_t outer, uint32_t bi, uint32_t bo, bool swz = true) {
  cuuint64_t dims[2] = {inner, outer};
  cuuint64_t strides[1] = {inner * 2};
  cuuint32_t box[2] = {bi, bo};
  enc(fn, m, base, 2, dims, strides, box, swz);
}

}

extern "C" void kernel_launch(void* const* d_in, const int* in_sizes, int n_in, void* d_out, int out_size) {
  (void)in_sizes; (void)n_in; (void)out_size;
  static Params P;
  static bool init = false, smap = false;
  static const void* last[9] = {};
  bool same = init;
  for (int i = 0; i < 8; i++) same = same && (last[i] == d_in[i]);
  same = same && (last[8] == d_out);
  if (!same) {
    void* fnp = nullptr;
    cudaDriverEntryPointQueryResult q;
    cudaGetDriverEntryPoint("cuTensorMapEncodeTiled", &fnp, cudaEnableDefault, &q);
    EncodeFn fn = (EncodeFn)fnp;
    void *pT, *pTE, *pC, *pX1, *pZ, *pH;
    cudaGetSymbolAddress(&pT, g_T);
    cudaGetSymbolAddress(&pTE, g_TE);
    cudaGetSymbolAddress(&pC, g_C);
    void* pS;
    cudaGetSymbolAddress(&pS, g_s);
    pX1 = (uint8_t*)pS + offsetof(Scratch, x1t);
    pZ = (uint8_t*)pS + offsetof(Scratch, zt);
    pH = (uint8_t*)pS + offsetof(Scratch, h);
    enc2(fn, &P.x, d_in[0], 640, 2048, 64, 128);
    for (int i = 0; i < 2; i++) {
      cuuint64_t dims[3] = {64, 640, 27};
      cuuint64_t strides[2] = {3456, 128};
      cuuint32_t box[3] = {64, 64, 2};
      enc(fn, i ? &P.wu : &P.wg, d_in[4 + i], 3, dims, strides, box, true);
    }
    enc2(fn, &P.wgh, d_in[4], 1728, 640, 64, 64);
    enc2(fn, &P.wuh, d_in[5], 1728, 640, 64, 64);
    enc2(fn, &P.tA, pT, 640, 640, 64, 128);
    enc2(fn, &P.x1st, pX1, 2048, 640, 64, 64);
    enc2(fn, &P.x1ld, pX1, 64, 20480, 64, 64);
    enc2(fn, &P.x1ld2, pX1, 64, 20480, 64, 128);
    enc2(fn, &P.zst32, pZ, 64, 20480, 64, 32);
    enc2(fn, &P.zst64, pZ, 64, 20480, 64, 64);
    {
      cuuint64_t dims[3] = {64, 640, 32};
      cuuint64_t strides[2] = {4096, 128};
      cuuint32_t box[3] = {64, 64, 2};
      enc(fn, &P.zld, pZ, 3, dims, strides, box, true);
    }
    enc2(fn, &P.hst, pH, 1728, 2048, 64, 64);
    enc2(fn, &P.hld, pH, 1728, 2048, 64, 128);
    enc2(fn, &P.wd, d_in[6], 640, 1728, 64, 64);
    enc2(fn, &P.wd32, d_in[6], 640, 1728, 32, 64);
    enc2(fn, &P.wr2, d_in[1], 32 * 321, 64, 168, 16, false);
    enc2(fn, &P.wi2, d_in[2], 32 * 321, 64, 168, 16, false);
    P.xp = (const uint16_t*)d_in[0];
    P.gw = (const uint16_t*)d_in[7];
    P.wdp = (const uint16_t*)d_in[6];
    P.TEp = (const uint16_t*)pTE;
    P.Cp = (const CConst*)pC;
    P.outp = (uint16_t*)d_out;
    int dev = 0, sms = 0;
    cudaGetDevice(&dev);
    cudaDeviceGetAttribute(&sms, cudaDevAttrMultiProcessorCount, dev);
    smap = sms == NCTA;
    cudaFuncSetAttribute(fused_kernel<true>, cudaFuncAttributeMaxDynamicSharedMemorySize, SMEM_BYTES);
    cudaFuncSetAttribute(fused_kernel<false>, cudaFuncAttributeMaxDynamicSharedMemorySize, SMEM_BYTES);
    for (int i = 0; i < 8; i++) last[i] = d_in[i];
    last[8] = d_out;
    init = true;
  }
  if (smap) fused_kernel<true><<<NCTA, 384, SMEM_BYTES, cudaStreamPerThread>>>(P);
  else fused_kernel<false><<<NCTA, 384, SMEM_BYTES, cudaStreamPerThread>>>(P);
}
```
